```python
import torch

def _softmax(x, axis=-1):
    return torch.softmax(x, dim=axis)
def _gelu(x):
    return torch.nn.functional.gelu(x, approximate="tanh")
def _silu(x):
    return torch.nn.functional.silu(x)
def _sigmoid(x):
    return torch.sigmoid(x)
def _layernorm(x, axis=-1, eps=1e-5):
    m = x.mean(dim=axis, keepdim=True)
    v = x.var(dim=axis, keepdim=True, unbiased=False)
    return (x - m) / torch.sqrt(v + eps)
def _scatter_add(tgt, idx, src, axis=0):
    return tgt.clone().index_add_(axis, idx, src)
def _segment_sum(src, seg, n):
    out = torch.zeros((n,) + src.shape[1:], dtype=src.dtype)
    return out.index_add_(0, seg, src)
def _pad(x, pw):
    flat = tuple(v for pair in reversed(pw) for v in pair)
    return torch.nn.functional.pad(x, flat)

kernel_name = 'sequential_preLN__ssm_conv_h3__swiglu_ffn__prompt'

def setup_inputs():

    _w = (lambda a: (lambda t: t.to(torch.bfloat16) if t.is_floating_point() else t)(torch.as_tensor(a)))
    def _A_setup():
        B, S, D = 1, 2048, 512
        ks = 4
        return {
            "q": _w((lambda *s: torch.randn(*s, dtype=torch.bfloat16) * 0.05)(B, S, D)),
            "k": _w((lambda *s: torch.randn(*s, dtype=torch.bfloat16) * 0.4)(B, S, D)),
            "v": _w((lambda *s: torch.randn(*s, dtype=torch.bfloat16) * 0.4)(B, S, D)),
            "shift_k": _w((lambda *s: torch.randn(*s, dtype=torch.bfloat16) * 0.4)(D, ks) * 0.5),
            "ssm_k": _w((lambda *s: torch.randn(*s, dtype=torch.bfloat16) * 0.4)(D, S) * (1.0 / S ** 0.5)),
            "ssm_D": _w((lambda *s: torch.randn(*s, dtype=torch.bfloat16) * 0.4)(D)),
        }
    _A_in = _A_setup()

    def _B_setup():
        B, S, D, F = 1, 2048, 512, 1376
        return {
            "x": _w((lambda *s: torch.randn(*s, dtype=torch.bfloat16) * 0.05)(B, S, D)),
            "w_gate": _w((lambda *s: torch.randn(*s, dtype=torch.bfloat16) * 0.05)(D, F)),
            "w_up": _w((lambda *s: torch.randn(*s, dtype=torch.bfloat16) * 0.05)(D, F)),
            "w_down": _w((lambda *s: torch.randn(*s, dtype=torch.bfloat16) * 0.05)(F, D)),
        }
    _B_in = _B_setup()

    return {
        "A_q": _A_in["q"],
        "A_k": _A_in["k"],
        "A_v": _A_in["v"],
        "A_shift_k": _A_in["shift_k"],
        "A_ssm_k": _A_in["ssm_k"],
        "A_ssm_D": _A_in["ssm_D"],
        "B_x": _B_in["x"],
        "B_w_gate": _B_in["w_gate"],
        "B_w_up": _B_in["w_up"],
        "B_w_down": _B_in["w_down"],
    }

def reference(A_q, A_k, A_v, A_shift_k, A_ssm_k, A_ssm_D, B_x, B_w_gate, B_w_up, B_w_down):
    def _A_ref(q, k, v, shift_k, ssm_k, ssm_D):
        B, S, D = q.shape
        ks = shift_k.shape[-1]
        k_pad = _pad(k, ((0, 0), (ks - 1, 0), (0, 0)))
        k_shift = torch.zeros_like(k)
        for t in range(ks):
            k_shift = k_shift + k_pad[:, t:t + S, :] * shift_k[:, ks - 1 - t][None, None, :]
        kv = k_shift * v
        L = 2 * S
        kv_pad = _pad(kv, ((0, 0), (0, S), (0, 0)))
        kf_pad = _pad(ssm_k, ((0, 0), (0, S)))
        kv_f = (lambda x, axes=(-2,-1): torch.fft.rfft2(x.float(), dim=axes))(kv_pad[:, None, :, :], axes=(1, 2))
        kf_f = (lambda x, axes=(-2,-1): torch.fft.rfft2(x.float(), dim=axes))(kf_pad[:, None, :], axes=(1, 2))
        kf_f = (lambda x, *d: x.permute(*d))(kf_f, 1, 2, 0)
        y_f = kv_f * kf_f[None, :, :, :]
        y = (lambda x, s, axes=(-2,-1): torch.fft.irfft2(x, s=s, dim=axes).to(torch.bfloat16))(y_f, (1, L), axes=(1, 2))[:, 0, :S, :]
        y = y + kv * ssm_D[None, None, :]
        return q * y

    def _B_ref(x, w_gate, w_up, w_down):
        g = _silu(x @ w_gate)
        u = x @ w_up
        return (g * u) @ w_down

    x = A_q
    h = x + _A_ref(_layernorm(x, axis=-1), A_k, A_v, A_shift_k, A_ssm_k, A_ssm_D)
    h2 = h + _B_ref(_layernorm(h, axis=-1), B_w_gate, B_w_up, B_w_down)
    return h2
```

```cpp
#include <cuda_runtime.h>
#include <cuda_bf16.h>
#include <cuda.h>
#include <stdint.h>

namespace {

constexpr int S_LEN = 2048, DM = 512, FF = 1376;
constexpr int NHELP = 4, NMAIN = 128;

constexpr uint32_t XR = 0, WR = 131072, MISC = 229376, SMEM_TOTAL = 232448;
constexpr uint32_t RAWK = 0, RAWK_BLK = 2176, RAWV = 17408, KRAW2 = 40960;
constexpr uint32_t KPAD = 65536, KT = KPAD + 4096, XT = KT + 16384, UPAD = XT + 16384, UT = UPAD + 128, QST = UT + 16384;
constexpr uint32_t RAWQ = 49152, QSLAB = WR + 2 * 16384, RED = WR + 3 * 16384, RED_WG = 17408, KRAW = RED + 1024;
constexpr uint32_t BARS = MISC, CSM = MISC + 512;
constexpr int B_RAWF = 0  , B_RAWQF = 8  , B_KFF = 12  , B_QSLAB = 14, B_QST = 15, B_UF = 16  , B_XQF = 20,
              B_RAWDONE = 21, B_CONVDONE = 22, B_CS = 23, B_EXCH = 24, B_WF = 25  , B_WE = 28  ,
              B_XF = 31  , B_XE = 35  , B_SIG = 39  ;
constexpr int NB_WG = 1  , NB_INIT = 3, NB_TURN = 5  ;

struct __align__(64) Params {
  CUtensorMap tmK, tmV, tmQ, tmWg, tmWu, tmWd, tmH, tmR, tmOut;
  const __nv_bfloat16 *q, *shiftk, *ssmk, *ssmD, *wd;
  __nv_bfloat16 *hT, *act;
  unsigned *qstat, *cnt;
  float* colsum;
  unsigned char role[NMAIN / 2];
};

__device__ __align__(1024) __nv_bfloat16 g_hT[DM * S_LEN];
__device__ __align__(1024) __nv_bfloat16 g_act[16 * 22 * 8192];
__device__ __align__(128) unsigned g_qstat[S_LEN];
__device__ __align__(128) float g_colsum[8 * 1408];
constexpr int CNT_STRIDE = 64;
constexpr int C_H = 0, C_A = 8, C_CS = 56, C_DONE = 57;
__device__ __align__(256) unsigned g_cnt[64 * CNT_STRIDE];
#define TLREC(i) do { } while (0)
#define TLONE(i) do { } while (0)
#define TLW(i) do { } while (0)
#define TL2(i) do { } while (0)

#define TLC(i) do { } while (0)

__device__ __forceinline__ uint32_t smem_u32(const void* p) { return (uint32_t)__cvta_generic_to_shared(p); }
__device__ __forceinline__ void mbar_init(uint32_t bar, uint32_t cnt) { asm volatile("mbarrier.init.shared::cta.b64 [%0], %1;" ::"r"(bar), "r"(cnt) : "memory"); }
__device__ __forceinline__ void mbar_expect(uint32_t bar, uint32_t bytes) { asm volatile("mbarrier.arrive.expect_tx.shared::cta.b64 _, [%0], %1;" ::"r"(bar), "r"(bytes) : "memory"); }
__device__ __forceinline__ void mbar_arrive(uint32_t bar) { asm volatile("mbarrier.arrive.shared::cta.b64 _, [%0];" ::"r"(bar) : "memory"); }
#define SPIN_LIMIT_STR "2000000"
constexpr int SPIN_LIMIT = 4000000;
__device__ __forceinline__ void mbar_wait_aux(uint32_t bar, uint32_t parity) {
  asm volatile("{\n.reg .pred p;\n.reg .u32 c;\nmov.u32 c, 0;\nLW_%=:\n"
               "mbarrier.try_wait.parity.shared::cta.b64 p, [%0], %1;\n@p bra LD_%=;\n"
               "add.u32 c, c, 1;\nsetp.gt.u32 p, c, " SPIN_LIMIT_STR ";\n@p trap;\nbra LW_%=;\nLD_%=:\n}" ::"r"(bar), "r"(parity) : "memory");
}
__device__ __forceinline__ void mbar_wait(uint32_t bar, uint32_t parity) {
  asm volatile("{\n.reg .pred p;\n.reg .u32 c;\nmov.u32 c, 0;\nLW_%=:\n"
               "mbarrier.try_wait.parity.shared::cta.b64 p, [%0], %1;\n@p bra LD_%=;\n"
               "add.u32 c, c, 1;\nsetp.le.u32 p, c, 4000000;\n@p bra LW_%=;\nLD_%=:\n}" ::"r"(bar), "r"(parity) : "memory");
}
__device__ __forceinline__ void mbar_wait_cl(uint32_t bar, uint32_t parity) {
  asm volatile("{\n.reg .pred p;\n.reg .u32 c;\nmov.u32 c, 0;\nLW_%=:\n"
               "mbarrier.try_wait.parity.acquire.cluster.shared::cta.b64 p, [%0], %1;\n@p bra LD_%=;\n"
               "add.u32 c, c, 1;\nsetp.le.u32 p, c, 4000000;\n@p bra LW_%=;\nLD_%=:\n}" ::"r"(bar), "r"(parity) : "memory");
}
__device__ __forceinline__ void poll_cnt(const unsigned* p, unsigned target) {
  asm volatile("{\n.reg .pred p;\n.reg .u32 c, v;\n.reg .s32 d;\nmov.u32 c, 0;\nLW_%=:\n"
               "ld.acquire.gpu.global.u32 v, [%0];\nsub.s32 d, v, %1;\nsetp.ge.s32 p, d, 0;\n@p bra LD_%=;\n"
               "add.u32 c, c, 1;\nsetp.gt.u32 p, c, " SPIN_LIMIT_STR ";\n@p trap;\nbra LW_%=;\nLD_%=:\n}" ::"l"(p), "r"(target) : "memory");
}
__device__ __forceinline__ void trap_if(bool c) { asm volatile("{\n.reg .pred p;\nsetp.ne.u32 p, %0, 0;\n@p trap;\n}" ::"r"((uint32_t)c)); }
__device__ __forceinline__ void red_release(unsigned* p) {
  asm volatile("fence.proxy.async;\nred.relaxed.gpu.global.add.u32 [%0], 1;" ::"l"(p) : "memory");
}
__device__ __forceinline__ void fence_async() { asm volatile("fence.proxy.async.global;" ::: "memory"); }
__device__ __forceinline__ void fence_async_smem() { asm volatile("fence.proxy.async.shared::cta;" ::: "memory"); }
__device__ __forceinline__ void nb_sync(int id, int n) { asm volatile("bar.sync %0, %1;" ::"r"(id), "r"(n) : "memory"); }
__device__ __forceinline__ void nb_arrive(int id, int n) { asm volatile("bar.arrive %0, %1;" ::"r"(id), "r"(n) : "memory"); }
__device__ __forceinline__ bool elect_one() {
  uint32_t p;
  asm volatile("{\n.reg .pred P;\nelect.sync _|P, 0xffffffff;\nselp.b32 %0, 1, 0, P;\n}" : "=r"(p));
  return p != 0;
}
__device__ __forceinline__ void stsm4t(uint32_t addr, uint32_t a, uint32_t b, uint32_t c, uint32_t d) {
  asm volatile("stmatrix.sync.aligned.m8n8.x4.trans.shared.b16 [%0], {%1,%2,%3,%4};" ::"r"(addr), "r"(a), "r"(b), "r"(c), "r"(d) : "memory");
}
__device__ __forceinline__ uint4 ldg_relaxed4(const void* p) {
  uint4 v;
  asm volatile("ld.relaxed.gpu.global.v4.u32 {%0,%1,%2,%3}, [%4];" : "=r"(v.x), "=r"(v.y), "=r"(v.z), "=r"(v.w) : "l"(p) : "memory");
  return v;
}
__device__ __forceinline__ unsigned ldg_relaxed(const unsigned* p) {
  unsigned v;
  asm volatile("ld.relaxed.gpu.global.u32 %0, [%1];" : "=r"(v) : "l"(p) : "memory");
  return v;
}
__device__ __forceinline__ uint32_t mapa(uint32_t a, uint32_t r) { uint32_t o; asm("mapa.shared::cluster.u32 %0, %1, %2;" : "=r"(o) : "r"(a), "r"(r)); return o; }
__device__ __forceinline__ void tma2d(uint32_t dst, const CUtensorMap* tm, uint32_t bar, int c0, int c1) {
  asm volatile("cp.async.bulk.tensor.2d.shared::cluster.global.mbarrier::complete_tx::bytes [%0], [%1, {%3,%4}], [%2];" ::"r"(dst), "l"(tm), "r"(bar), "r"(c0), "r"(c1) : "memory");
}
__device__ __forceinline__ void tma3d(uint32_t dst, const CUtensorMap* tm, uint32_t bar, int c0, int c1, int c2) {
  asm volatile("cp.async.bulk.tensor.3d.shared::cluster.global.mbarrier::complete_tx::bytes [%0], [%1, {%3,%4,%5}], [%2];" ::"r"(dst), "l"(tm), "r"(bar), "r"(c0), "r"(c1), "r"(c2) : "memory");
}
__device__ __forceinline__ void tma3d_mc(uint32_t dst, const CUtensorMap* tm, uint32_t bar, int c0, int c1, int c2) {
  asm volatile("cp.async.bulk.tensor.3d.shared::cluster.global.mbarrier::complete_tx::bytes.multicast::cluster [%0], [%1, {%3,%4,%5}], [%2], %6;" ::"r"(dst), "l"(tm), "r"(bar), "r"(c0), "r"(c1), "r"(c2), "h"((uint16_t)3) : "memory");
}
__device__ __forceinline__ void mbar_arrive_cl(uint32_t bar) { asm volatile("mbarrier.arrive.shared::cluster.b64 _, [%0];" ::"r"(bar) : "memory"); }
__device__ __forceinline__ uint32_t bsub2(uint32_t a, uint32_t b) { uint32_t d; asm("sub.rn.bf16x2 %0, %1, %2;" : "=r"(d) : "r"(a), "r"(b)); return d; }
__device__ __forceinline__ uint32_t bfma2(uint32_t a, uint32_t b, uint32_t c) { uint32_t d; asm("fma.rn.bf16x2 %0, %1, %2, %3;" : "=r"(d) : "r"(a), "r"(b), "r"(c)); return d; }
__device__ __forceinline__ void bulk_ld(uint32_t dst, const void* src, uint32_t bytes, uint32_t bar) {
  asm volatile("cp.async.bulk.shared::cluster.global.mbarrier::complete_tx::bytes [%0], [%1], %2, [%3];" ::"r"(dst), "l"(src), "r"(bytes), "r"(bar) : "memory");
}
__device__ __forceinline__ void l2_prefetch(const void* src, uint32_t bytes) { asm volatile("cp.async.bulk.prefetch.L2.global [%0], %1;" ::"l"(src), "r"(bytes) : "memory"); }
__device__ __forceinline__ void ldsm4t(uint32_t* r, uint32_t addr) {
  asm volatile("ldmatrix.sync.aligned.m8n8.x4.trans.shared.b16 {%0,%1,%2,%3}, [%4];" : "=r"(r[0]), "=r"(r[1]), "=r"(r[2]), "=r"(r[3]) : "r"(addr) : "memory");
}
__device__ __forceinline__ void ldsm2t(uint32_t* r, uint32_t addr) {
  asm volatile("ldmatrix.sync.aligned.m8n8.x2.trans.shared.b16 {%0,%1}, [%2];" : "=r"(r[0]), "=r"(r[1]) : "r"(addr) : "memory");
}
__device__ __forceinline__ void stsm4(uint32_t addr, uint32_t a, uint32_t b, uint32_t c, uint32_t d) {
  asm volatile("stmatrix.sync.aligned.m8n8.x4.shared.b16 [%0], {%1,%2,%3,%4};" ::"r"(addr), "r"(a), "r"(b), "r"(c), "r"(d) : "memory");
}
__device__ __forceinline__ uint32_t lds32(uint32_t a) { uint32_t v; asm volatile("ld.shared.b32 %0, [%1];" : "=r"(v) : "r"(a) : "memory"); return v; }
__device__ __forceinline__ float2 lds64f(uint32_t a) { float2 v; asm volatile("ld.shared.v2.f32 {%0,%1}, [%2];" : "=f"(v.x), "=f"(v.y) : "r"(a) : "memory"); return v; }
__device__ __forceinline__ uint4 lds128(uint32_t a) { uint4 v; asm volatile("ld.shared.v4.b32 {%0,%1,%2,%3}, [%4];" : "=r"(v.x), "=r"(v.y), "=r"(v.z), "=r"(v.w) : "r"(a) : "memory"); return v; }
__device__ __forceinline__ void sts64f(uint32_t a, float x, float y) { asm volatile("st.shared.v2.f32 [%0], {%1,%2};" ::"r"(a), "f"(x), "f"(y) : "memory"); }
__device__ __forceinline__ void sts128(uint32_t a, uint32_t x, uint32_t y, uint32_t z, uint32_t w) { asm volatile("st.shared.v4.b32 [%0], {%1,%2,%3,%4};" ::"r"(a), "r"(x), "r"(y), "r"(z), "r"(w) : "memory"); }
__device__ __forceinline__ void st_async4(uint32_t a, const uint32_t* v, uint32_t bar) {
  asm volatile("st.async.weak.shared::cluster.mbarrier::complete_tx::bytes.v4.b32 [%0], {%1,%2,%3,%4}, [%5];" ::"r"(a), "r"(v[0]), "r"(v[1]), "r"(v[2]), "r"(v[3]), "r"(bar) : "memory");
}
__device__ __forceinline__ uint32_t prmt(uint32_t a, uint32_t b, uint32_t s) { uint32_t d; asm("prmt.b32 %0, %1, %2, %3;" : "=r"(d) : "r"(a), "r"(b), "r"(s)); return d; }
__device__ __forceinline__ uint32_t bmul2(uint32_t a, uint32_t b) { uint32_t d; asm("mul.rn.bf16x2 %0, %1, %2;" : "=r"(d) : "r"(a), "r"(b)); return d; }
__device__ __forceinline__ uint32_t badd2(uint32_t a, uint32_t b) { uint32_t d; asm("add.rn.bf16x2 %0, %1, %2;" : "=r"(d) : "r"(a), "r"(b)); return d; }
__device__ __forceinline__ uint32_t pack2(float lo, float hi) { uint32_t d; asm("cvt.rn.bf16x2.f32 %0, %1, %2;" : "=r"(d) : "f"(hi), "f"(lo)); return d; }
__device__ __forceinline__ float blo(uint32_t w) { return __uint_as_float(w << 16); }
__device__ __forceinline__ float bhi(uint32_t w) { return __uint_as_float(w & 0xffff0000u); }
__device__ __forceinline__ float bround(float x) { return __bfloat162float(__float2bfloat16_rn(x)); }
__device__ __forceinline__ float tanh_fast(float x) { float y; asm("tanh.approx.f32 %0, %1;" : "=f"(y) : "f"(x)); return y; }
__device__ __forceinline__ float sqrt_fast(float x) { float y; asm("sqrt.approx.f32 %0, %1;" : "=f"(y) : "f"(x)); return y; }
__device__ __forceinline__ float rcp_fast(float x) { float y; asm("rcp.approx.ftz.f32 %0, %1;" : "=f"(y) : "f"(x)); return y; }
__device__ __forceinline__ uint32_t mkdesc(uint32_t addr, uint32_t lbo) { return ((addr & 0x3FFFF) >> 4) | ((lbo >> 4) << 16); }
__device__ __forceinline__ void wg_fence() { asm volatile("wgmma.fence.sync.aligned;" ::: "memory"); }
__device__ __forceinline__ void wg_commit() { asm volatile("wgmma.commit_group.sync.aligned;" ::: "memory"); }
template <int N> __device__ __forceinline__ void wg_wait() { asm volatile("wgmma.wait_group.sync.aligned %0;" ::"n"(N) : "memory"); }
template <int N> __device__ __forceinline__ void reg_fence(float* d) {
#pragma unroll
  for (int i = 0; i < N; i++) asm volatile("" : "+f"(d[i])::"memory");
}

__device__ __forceinline__ void wg_conv0(float* d, const uint32_t* a, uint32_t db) {
  asm volatile("{.reg .b64 b; mov.b64 b, {%20, 0x40000040}; wgmma.mma_async.sync.aligned.m64n32k16.f32.bf16.bf16 {%0,%1,%2,%3,%4,%5,%6,%7,%8,%9,%10,%11,%12,%13,%14,%15}, {%16,%17,%18,%19}, b, 0, 1, 1, 0;}"
    : "=f"(d[0]),"=f"(d[1]),"=f"(d[2]),"=f"(d[3]),"=f"(d[4]),"=f"(d[5]),"=f"(d[6]),"=f"(d[7]),"=f"(d[8]),"=f"(d[9]),"=f"(d[10]),"=f"(d[11]),"=f"(d[12]),"=f"(d[13]),"=f"(d[14]),"=f"(d[15])
    : "r"(a[0]),"r"(a[1]),"r"(a[2]),"r"(a[3]),"r"(db));
}
__device__ __forceinline__ void wg_g1a0(float* d, uint32_t da, uint32_t db) {
  asm volatile("{.reg .b64 a, b; mov.b64 a, {%64, 0x40000040}; mov.b64 b, {%65, 0x40000040}; wgmma.mma_async.sync.aligned.m64n128k16.f32.bf16.bf16 {%0,%1,%2,%3,%4,%5,%6,%7,%8,%9,%10,%11,%12,%13,%14,%15,%16,%17,%18,%19,%20,%21,%22,%23,%24,%25,%26,%27,%28,%29,%30,%31,%32,%33,%34,%35,%36,%37,%38,%39,%40,%41,%42,%43,%44,%45,%46,%47,%48,%49,%50,%51,%52,%53,%54,%55,%56,%57,%58,%59,%60,%61,%62,%63}, a, b, 0, 1, 1, 1, 1;}"
    : "=f"(d[0]),"=f"(d[1]),"=f"(d[2]),"=f"(d[3]),"=f"(d[4]),"=f"(d[5]),"=f"(d[6]),"=f"(d[7]),"=f"(d[8]),"=f"(d[9]),"=f"(d[10]),"=f"(d[11]),"=f"(d[12]),"=f"(d[13]),"=f"(d[14]),"=f"(d[15]),"=f"(d[16]),"=f"(d[17]),"=f"(d[18]),"=f"(d[19]),"=f"(d[20]),"=f"(d[21]),"=f"(d[22]),"=f"(d[23]),"=f"(d[24]),"=f"(d[25]),"=f"(d[26]),"=f"(d[27]),"=f"(d[28]),"=f"(d[29]),"=f"(d[30]),"=f"(d[31]),"=f"(d[32]),"=f"(d[33]),"=f"(d[34]),"=f"(d[35]),"=f"(d[36]),"=f"(d[37]),"=f"(d[38]),"=f"(d[39]),"=f"(d[40]),"=f"(d[41]),"=f"(d[42]),"=f"(d[43]),"=f"(d[44]),"=f"(d[45]),"=f"(d[46]),"=f"(d[47]),"=f"(d[48]),"=f"(d[49]),"=f"(d[50]),"=f"(d[51]),"=f"(d[52]),"=f"(d[53]),"=f"(d[54]),"=f"(d[55]),"=f"(d[56]),"=f"(d[57]),"=f"(d[58]),"=f"(d[59]),"=f"(d[60]),"=f"(d[61]),"=f"(d[62]),"=f"(d[63])
    : "r"(da),"r"(db));
}
__device__ __forceinline__ void wg_g1b0(float* d, uint32_t da, uint32_t db) {
  asm volatile("{.reg .b64 a, b; mov.b64 a, {%56, 0x40000040}; mov.b64 b, {%57, 0x40000040}; wgmma.mma_async.sync.aligned.m64n112k16.f32.bf16.bf16 {%0,%1,%2,%3,%4,%5,%6,%7,%8,%9,%10,%11,%12,%13,%14,%15,%16,%17,%18,%19,%20,%21,%22,%23,%24,%25,%26,%27,%28,%29,%30,%31,%32,%33,%34,%35,%36,%37,%38,%39,%40,%41,%42,%43,%44,%45,%46,%47,%48,%49,%50,%51,%52,%53,%54,%55}, a, b, 0, 1, 1, 1, 1;}"
    : "=f"(d[0]),"=f"(d[1]),"=f"(d[2]),"=f"(d[3]),"=f"(d[4]),"=f"(d[5]),"=f"(d[6]),"=f"(d[7]),"=f"(d[8]),"=f"(d[9]),"=f"(d[10]),"=f"(d[11]),"=f"(d[12]),"=f"(d[13]),"=f"(d[14]),"=f"(d[15]),"=f"(d[16]),"=f"(d[17]),"=f"(d[18]),"=f"(d[19]),"=f"(d[20]),"=f"(d[21]),"=f"(d[22]),"=f"(d[23]),"=f"(d[24]),"=f"(d[25]),"=f"(d[26]),"=f"(d[27]),"=f"(d[28]),"=f"(d[29]),"=f"(d[30]),"=f"(d[31]),"=f"(d[32]),"=f"(d[33]),"=f"(d[34]),"=f"(d[35]),"=f"(d[36]),"=f"(d[37]),"=f"(d[38]),"=f"(d[39]),"=f"(d[40]),"=f"(d[41]),"=f"(d[42]),"=f"(d[43]),"=f"(d[44]),"=f"(d[45]),"=f"(d[46]),"=f"(d[47]),"=f"(d[48]),"=f"(d[49]),"=f"(d[50]),"=f"(d[51]),"=f"(d[52]),"=f"(d[53]),"=f"(d[54]),"=f"(d[55])
    : "r"(da),"r"(db));
}
__device__ __forceinline__ void wg_g20(float* d, uint32_t da, uint32_t db) {
  asm volatile("{.reg .b64 a, b; mov.b64 a, {%64, 0x00000040}; mov.b64 b, {%65, 0x40000040}; wgmma.mma_async.sync.aligned.m64n128k16.f32.bf16.bf16 {%0,%1,%2,%3,%4,%5,%6,%7,%8,%9,%10,%11,%12,%13,%14,%15,%16,%17,%18,%19,%20,%21,%22,%23,%24,%25,%26,%27,%28,%29,%30,%31,%32,%33,%34,%35,%36,%37,%38,%39,%40,%41,%42,%43,%44,%45,%46,%47,%48,%49,%50,%51,%52,%53,%54,%55,%56,%57,%58,%59,%60,%61,%62,%63}, a, b, 0, 1, 1, 0, 1;}"
    : "=f"(d[0]),"=f"(d[1]),"=f"(d[2]),"=f"(d[3]),"=f"(d[4]),"=f"(d[5]),"=f"(d[6]),"=f"(d[7]),"=f"(d[8]),"=f"(d[9]),"=f"(d[10]),"=f"(d[11]),"=f"(d[12]),"=f"(d[13]),"=f"(d[14]),"=f"(d[15]),"=f"(d[16]),"=f"(d[17]),"=f"(d[18]),"=f"(d[19]),"=f"(d[20]),"=f"(d[21]),"=f"(d[22]),"=f"(d[23]),"=f"(d[24]),"=f"(d[25]),"=f"(d[26]),"=f"(d[27]),"=f"(d[28]),"=f"(d[29]),"=f"(d[30]),"=f"(d[31]),"=f"(d[32]),"=f"(d[33]),"=f"(d[34]),"=f"(d[35]),"=f"(d[36]),"=f"(d[37]),"=f"(d[38]),"=f"(d[39]),"=f"(d[40]),"=f"(d[41]),"=f"(d[42]),"=f"(d[43]),"=f"(d[44]),"=f"(d[45]),"=f"(d[46]),"=f"(d[47]),"=f"(d[48]),"=f"(d[49]),"=f"(d[50]),"=f"(d[51]),"=f"(d[52]),"=f"(d[53]),"=f"(d[54]),"=f"(d[55]),"=f"(d[56]),"=f"(d[57]),"=f"(d[58]),"=f"(d[59]),"=f"(d[60]),"=f"(d[61]),"=f"(d[62]),"=f"(d[63])
    : "r"(da),"r"(db));
}
__device__ __forceinline__ void wg_conv(float* d, const uint32_t* a, uint32_t db) {
  asm volatile("{.reg .b64 b; mov.b64 b, {%20, 0x40000040}; wgmma.mma_async.sync.aligned.m64n32k16.f32.bf16.bf16 {%0,%1,%2,%3,%4,%5,%6,%7,%8,%9,%10,%11,%12,%13,%14,%15}, {%16,%17,%18,%19}, b, 1, 1, 1, 0;}"
    : "+f"(d[0]),"+f"(d[1]),"+f"(d[2]),"+f"(d[3]),"+f"(d[4]),"+f"(d[5]),"+f"(d[6]),"+f"(d[7]),"+f"(d[8]),"+f"(d[9]),"+f"(d[10]),"+f"(d[11]),"+f"(d[12]),"+f"(d[13]),"+f"(d[14]),"+f"(d[15])
    : "r"(a[0]),"r"(a[1]),"r"(a[2]),"r"(a[3]),"r"(db));
}
__device__ __forceinline__ void wg_g1r(float* d, const uint32_t* a, uint32_t db) {
  asm volatile("{.reg .b64 b; mov.b64 b, {%68, 0x40000040}; wgmma.mma_async.sync.aligned.m64n128k16.f32.bf16.bf16 {%0,%1,%2,%3,%4,%5,%6,%7,%8,%9,%10,%11,%12,%13,%14,%15,%16,%17,%18,%19,%20,%21,%22,%23,%24,%25,%26,%27,%28,%29,%30,%31,%32,%33,%34,%35,%36,%37,%38,%39,%40,%41,%42,%43,%44,%45,%46,%47,%48,%49,%50,%51,%52,%53,%54,%55,%56,%57,%58,%59,%60,%61,%62,%63}, {%64,%65,%66,%67}, b, 1, 1, 1, 1;}"
    : "+f"(d[0]),"+f"(d[1]),"+f"(d[2]),"+f"(d[3]),"+f"(d[4]),"+f"(d[5]),"+f"(d[6]),"+f"(d[7]),"+f"(d[8]),"+f"(d[9]),"+f"(d[10]),"+f"(d[11]),"+f"(d[12]),"+f"(d[13]),"+f"(d[14]),"+f"(d[15]),"+f"(d[16]),"+f"(d[17]),"+f"(d[18]),"+f"(d[19]),"+f"(d[20]),"+f"(d[21]),"+f"(d[22]),"+f"(d[23]),"+f"(d[24]),"+f"(d[25]),"+f"(d[26]),"+f"(d[27]),"+f"(d[28]),"+f"(d[29]),"+f"(d[30]),"+f"(d[31]),"+f"(d[32]),"+f"(d[33]),"+f"(d[34]),"+f"(d[35]),"+f"(d[36]),"+f"(d[37]),"+f"(d[38]),"+f"(d[39]),"+f"(d[40]),"+f"(d[41]),"+f"(d[42]),"+f"(d[43]),"+f"(d[44]),"+f"(d[45]),"+f"(d[46]),"+f"(d[47]),"+f"(d[48]),"+f"(d[49]),"+f"(d[50]),"+f"(d[51]),"+f"(d[52]),"+f"(d[53]),"+f"(d[54]),"+f"(d[55]),"+f"(d[56]),"+f"(d[57]),"+f"(d[58]),"+f"(d[59]),"+f"(d[60]),"+f"(d[61]),"+f"(d[62]),"+f"(d[63])
    : "r"(a[0]),"r"(a[1]),"r"(a[2]),"r"(a[3]),"r"(db));
}
__device__ __forceinline__ void wg_g1a(float* d, uint32_t da, uint32_t db) {
  asm volatile("{.reg .b64 a, b; mov.b64 a, {%64, 0x40000040}; mov.b64 b, {%65, 0x40000040}; wgmma.mma_async.sync.aligned.m64n128k16.f32.bf16.bf16 {%0,%1,%2,%3,%4,%5,%6,%7,%8,%9,%10,%11,%12,%13,%14,%15,%16,%17,%18,%19,%20,%21,%22,%23,%24,%25,%26,%27,%28,%29,%30,%31,%32,%33,%34,%35,%36,%37,%38,%39,%40,%41,%42,%43,%44,%45,%46,%47,%48,%49,%50,%51,%52,%53,%54,%55,%56,%57,%58,%59,%60,%61,%62,%63}, a, b, 1, 1, 1, 1, 1;}"
    : "+f"(d[0]),"+f"(d[1]),"+f"(d[2]),"+f"(d[3]),"+f"(d[4]),"+f"(d[5]),"+f"(d[6]),"+f"(d[7]),"+f"(d[8]),"+f"(d[9]),"+f"(d[10]),"+f"(d[11]),"+f"(d[12]),"+f"(d[13]),"+f"(d[14]),"+f"(d[15]),"+f"(d[16]),"+f"(d[17]),"+f"(d[18]),"+f"(d[19]),"+f"(d[20]),"+f"(d[21]),"+f"(d[22]),"+f"(d[23]),"+f"(d[24]),"+f"(d[25]),"+f"(d[26]),"+f"(d[27]),"+f"(d[28]),"+f"(d[29]),"+f"(d[30]),"+f"(d[31]),"+f"(d[32]),"+f"(d[33]),"+f"(d[34]),"+f"(d[35]),"+f"(d[36]),"+f"(d[37]),"+f"(d[38]),"+f"(d[39]),"+f"(d[40]),"+f"(d[41]),"+f"(d[42]),"+f"(d[43]),"+f"(d[44]),"+f"(d[45]),"+f"(d[46]),"+f"(d[47]),"+f"(d[48]),"+f"(d[49]),"+f"(d[50]),"+f"(d[51]),"+f"(d[52]),"+f"(d[53]),"+f"(d[54]),"+f"(d[55]),"+f"(d[56]),"+f"(d[57]),"+f"(d[58]),"+f"(d[59]),"+f"(d[60]),"+f"(d[61]),"+f"(d[62]),"+f"(d[63])
    : "r"(da),"r"(db));
}
__device__ __forceinline__ void wg_g1b(float* d, uint32_t da, uint32_t db) {
  asm volatile("{.reg .b64 a, b; mov.b64 a, {%56, 0x40000040}; mov.b64 b, {%57, 0x40000040}; wgmma.mma_async.sync.aligned.m64n112k16.f32.bf16.bf16 {%0,%1,%2,%3,%4,%5,%6,%7,%8,%9,%10,%11,%12,%13,%14,%15,%16,%17,%18,%19,%20,%21,%22,%23,%24,%25,%26,%27,%28,%29,%30,%31,%32,%33,%34,%35,%36,%37,%38,%39,%40,%41,%42,%43,%44,%45,%46,%47,%48,%49,%50,%51,%52,%53,%54,%55}, a, b, 1, 1, 1, 1, 1;}"
    : "+f"(d[0]),"+f"(d[1]),"+f"(d[2]),"+f"(d[3]),"+f"(d[4]),"+f"(d[5]),"+f"(d[6]),"+f"(d[7]),"+f"(d[8]),"+f"(d[9]),"+f"(d[10]),"+f"(d[11]),"+f"(d[12]),"+f"(d[13]),"+f"(d[14]),"+f"(d[15]),"+f"(d[16]),"+f"(d[17]),"+f"(d[18]),"+f"(d[19]),"+f"(d[20]),"+f"(d[21]),"+f"(d[22]),"+f"(d[23]),"+f"(d[24]),"+f"(d[25]),"+f"(d[26]),"+f"(d[27]),"+f"(d[28]),"+f"(d[29]),"+f"(d[30]),"+f"(d[31]),"+f"(d[32]),"+f"(d[33]),"+f"(d[34]),"+f"(d[35]),"+f"(d[36]),"+f"(d[37]),"+f"(d[38]),"+f"(d[39]),"+f"(d[40]),"+f"(d[41]),"+f"(d[42]),"+f"(d[43]),"+f"(d[44]),"+f"(d[45]),"+f"(d[46]),"+f"(d[47]),"+f"(d[48]),"+f"(d[49]),"+f"(d[50]),"+f"(d[51]),"+f"(d[52]),"+f"(d[53]),"+f"(d[54]),"+f"(d[55])
    : "r"(da),"r"(db));
}
__device__ __forceinline__ void wg_g2(float* d, uint32_t da, uint32_t db) {
  asm volatile("{.reg .b64 a, b; mov.b64 a, {%64, 0x00000040}; mov.b64 b, {%65, 0x40000040}; wgmma.mma_async.sync.aligned.m64n128k16.f32.bf16.bf16 {%0,%1,%2,%3,%4,%5,%6,%7,%8,%9,%10,%11,%12,%13,%14,%15,%16,%17,%18,%19,%20,%21,%22,%23,%24,%25,%26,%27,%28,%29,%30,%31,%32,%33,%34,%35,%36,%37,%38,%39,%40,%41,%42,%43,%44,%45,%46,%47,%48,%49,%50,%51,%52,%53,%54,%55,%56,%57,%58,%59,%60,%61,%62,%63}, a, b, 1, 1, 1, 0, 1;}"
    : "+f"(d[0]),"+f"(d[1]),"+f"(d[2]),"+f"(d[3]),"+f"(d[4]),"+f"(d[5]),"+f"(d[6]),"+f"(d[7]),"+f"(d[8]),"+f"(d[9]),"+f"(d[10]),"+f"(d[11]),"+f"(d[12]),"+f"(d[13]),"+f"(d[14]),"+f"(d[15]),"+f"(d[16]),"+f"(d[17]),"+f"(d[18]),"+f"(d[19]),"+f"(d[20]),"+f"(d[21]),"+f"(d[22]),"+f"(d[23]),"+f"(d[24]),"+f"(d[25]),"+f"(d[26]),"+f"(d[27]),"+f"(d[28]),"+f"(d[29]),"+f"(d[30]),"+f"(d[31]),"+f"(d[32]),"+f"(d[33]),"+f"(d[34]),"+f"(d[35]),"+f"(d[36]),"+f"(d[37]),"+f"(d[38]),"+f"(d[39]),"+f"(d[40]),"+f"(d[41]),"+f"(d[42]),"+f"(d[43]),"+f"(d[44]),"+f"(d[45]),"+f"(d[46]),"+f"(d[47]),"+f"(d[48]),"+f"(d[49]),"+f"(d[50]),"+f"(d[51]),"+f"(d[52]),"+f"(d[53]),"+f"(d[54]),"+f"(d[55]),"+f"(d[56]),"+f"(d[57]),"+f"(d[58]),"+f"(d[59]),"+f"(d[60]),"+f"(d[61]),"+f"(d[62]),"+f"(d[63])
    : "r"(da),"r"(db));
}

template <int S> __device__ __forceinline__ void conv_mma(float* acc, const uint32_t (*A)[4], uint32_t d0) {
  wg_fence();
#pragma unroll
  for (int e = 0; e < 8; e++) {
#pragma unroll
    for (int i = 0; i < 4 - S; i++) {
      if (S == 0 && e == 0) wg_conv0(acc + 16 * i, A[e], d0 + (32 * i + 32) * 8);
      else wg_conv(acc + 16 * (i + S), A[e], d0 + (32 * i - 4 * e + 32) * 8);
    }
  }
  wg_commit();
}
__device__ __forceinline__ void conv_loadA(uint32_t (*A)[4], const uint32_t* ua, uint32_t off) {
#pragma unroll
  for (int e = 0; e < 8; e++) {
    const uint32_t e0 = lds32(ua[0] + off + 512 * e), e1 = lds32(ua[1] + off + 512 * e), e2 = lds32(ua[2] + off + 512 * e);
    A[e][0] = prmt(e0, e1, 0x5432);
    A[e][1] = e1;
    A[e][2] = prmt(e1, e2, 0x5432);
    A[e][3] = e2;
  }
}
__device__ __forceinline__ void filter_block(uint32_t src, uint32_t dst) {
  const uint4 a = lds128(src), c = lds128(src + 16);
  sts128(dst, prmt(c.w, 0, 0x1032), prmt(c.y, 0, 0x1032), prmt(a.w, 0, 0x1032), prmt(a.y, 0, 0x1032));
  sts128(dst ^ 16, prmt(c.z, 0, 0x1032), prmt(c.x, 0, 0x1032), prmt(a.z, 0, 0x1032), prmt(a.x, 0, 0x1032));
}

struct RowStat { float m0, r0, h0, m1, r1, h1; };

template <int NG> __device__ __forceinline__ void load_cs(float2* cs, uint32_t a) {
#pragma unroll
  for (int j = 0; j < NG; j++) { cs[j] = lds64f(a + j * 32); cs[8 + j] = lds64f(a + 256 + j * 32); }
}
template <int J0, int J1, bool TAIL>
__device__ __forceinline__ void ffn_epi(const float* acc, const float2* cs, const RowStat& rs, uint32_t* dst, int kg0, int ng) {
#pragma unroll
  for (int j = J0; j < J1; j++) {
    float a[4];
#pragma unroll
    for (int e = 0; e < 4; e++) {
      const float m = (e & 2) ? rs.m1 : rs.m0, r = (e & 2) ? rs.r1 : rs.r0, h = (e & 2) ? rs.h1 : rs.h0;
      const float gh = fmaf(-m, (e & 1) ? cs[j].y : cs[j].x, acc[4 * j + e]) * h;
      const float u = fmaf(-m, (e & 1) ? cs[8 + j].y : cs[8 + j].x, acc[32 + 4 * j + e]) * r;
      a[e] = fmaf(gh, tanh_fast(gh), gh) * u;
    }
    if (!TAIL) {
      dst[j * 32] = pack2(a[0], a[1]);
      dst[j * 32 + 256] = pack2(a[2], a[3]);
    } else if (j < ng) {
      const int kg = kg0 + j;
      uint32_t* p = dst + (kg >> 3) * 4096 + (kg & 7) * 32;
      p[0] = pack2(a[0], a[1]);
      p[256] = pack2(a[2], a[3]);
    }
  }
}

#define BAR(i) (bars + 8u * (uint32_t)(i))
#define QST_POS 4
#define AHEAD 3
#define HELPER_DELAY 5000

template <int KIND, int NKS, bool FIRST>
__device__ __forceinline__ void mma_unit(float* acc, uint32_t da, uint32_t db) {
  asm volatile("" : "+r"(da), "+r"(db));
  wg_fence();
#pragma unroll
  for (int ks = 0; ks < NKS; ks++) {
    const uint32_t a = da + (ks >> 2) * 1024 + (ks & 3) * (KIND == 2 ? 16 : 128), b = db + (ks >> 2) * 1024 + (ks & 3) * 128;
    if (FIRST && ks == 0) { if (KIND == 0) wg_g1a0(acc, a, b); else if (KIND == 1) wg_g1b0(acc, a, b); else wg_g20(acc, a, b); }
    else { if (KIND == 0) wg_g1a(acc, a, b); else if (KIND == 1) wg_g1b(acc, a, b); else wg_g2(acc, a, b); }
  }
  wg_commit();
}
__device__ __forceinline__ void mma_unit_rs(float* acc, const uint32_t (*f)[4], uint32_t db) {
  asm volatile("" : "+r"(db));
  wg_fence();
#pragma unroll
  for (int ks = 0; ks < 8; ks++) wg_g1r(acc, f[ks], db + (ks >> 2) * 1024 + (ks & 3) * 128);
  wg_commit();
}
__device__ __forceinline__ void load_frags(uint32_t (*f)[4], uint32_t a) {
#pragma unroll
  for (int ks = 0; ks < 8; ks++) ldsm4t(f[ks], a + (ks >> 2) * 16384 + (ks & 3) * 2048);
}
__device__ __forceinline__ void row_stats(const uint32_t (*f)[4], float* hs, float* hq) {
#pragma unroll
  for (int ks = 0; ks < 8; ks++) {
#pragma unroll
    for (int e = 0; e < 4; e++) {
      const float lo = blo(f[ks][e]), hi = bhi(f[ks][e]);
      hs[e] += lo + hi; hq[e] = fmaf(lo, lo, fmaf(hi, hi, hq[e]));
    }
  }
  reg_fence<4>(hs);
  reg_fence<4>(hq);
}

__global__ void __cluster_dims__(2, 1, 1) __launch_bounds__(384, 1) fused_kernel(const __grid_constant__ Params P) {
  extern __shared__ __align__(1024) unsigned char smem_raw[];
  const uint32_t sb = smem_u32(smem_raw);
  const int tid = threadIdx.x, lane = tid & 31;
  const int warp = __shfl_sync(0xffffffffu, tid >> 5, 0);
  const uint32_t bars = sb + BARS;

  if (blockIdx.x < NHELP) {
    const CUtensorMap* tm = (blockIdx.x >> 1) ? &P.tmWu : &P.tmWg;
    const uint32_t hb = BAR(2 * warp), buf = sb + warp * 16384;
    const int sub = 2 * (blockIdx.x & 1) + (warp & 1);
    if (elect_one()) {
      mbar_init(hb, 1); mbar_init(hb + 8, 1);
      fence_async_smem();
      const long long t0 = clock64();
      while (clock64() - t0 < HELPER_DELAY) { }
      mbar_expect(hb, 8192);
      tma3d(buf, tm, hb, 64 * (warp >> 1), sub, 0);
      mbar_expect(hb + 8, 8192);
      tma3d(buf + 8192, tm, hb + 8, 64 * (warp >> 1), sub, 64);
    }
    __syncwarp();
    const uint32_t a0 = buf + (lane >> 3) * 128 + (((lane & 7) ^ (lane >> 3)) << 4), a1 = buf + ((lane >> 3) + 4) * 128 + (((lane & 7) ^ ((lane >> 3) + 4)) << 4);
    uint32_t par = 0;
#pragma unroll 1
    for (int u = warp; u < 44; u += 12) {
      float s[8];
#pragma unroll
      for (int i = 0; i < 8; i++) s[i] = 0.f;
#pragma unroll 1
      for (int hf = 0; hf < 2; hf++) {
        mbar_wait_aux(hb + 8 * hf, par);
        uint4 v[8], w[8];
#pragma unroll
        for (int i = 0; i < 8; i++) { v[i] = lds128(a0 + hf * 8192 + i * 1024); w[i] = lds128(a1 + hf * 8192 + i * 1024); }
#pragma unroll
        for (int i = 0; i < 8; i++) {
          s[0] += blo(v[i].x) + blo(w[i].x); s[1] += bhi(v[i].x) + bhi(w[i].x); s[2] += blo(v[i].y) + blo(w[i].y); s[3] += bhi(v[i].y) + bhi(w[i].y);
          s[4] += blo(v[i].z) + blo(w[i].z); s[5] += bhi(v[i].z) + bhi(w[i].z); s[6] += blo(v[i].w) + blo(w[i].w); s[7] += bhi(v[i].w) + bhi(w[i].w);
          if (i == 7) {
            __syncwarp();
            if (u + 12 < 44 && elect_one()) {
              mbar_expect(hb + 8 * hf, 8192);
              tma3d(buf + hf * 8192, tm, hb + 8 * hf, 64 * ((u + 12) >> 1), sub, 64 * hf);
            }
          }
        }
      }
      par ^= 1;
#pragma unroll
      for (int i = 0; i < 8; i++) { s[i] += __shfl_xor_sync(0xffffffffu, s[i], 8); s[i] += __shfl_xor_sync(0xffffffffu, s[i], 16); }
      if (lane < 8) {
        float4* o = reinterpret_cast<float4*>(P.colsum + (blockIdx.x * 2 + (u & 1)) * 1408 + 64 * (u >> 1) + 8 * lane);
        o[0] = make_float4(s[0], s[1], s[2], s[3]); o[1] = make_float4(s[4], s[5], s[6], s[7]);
      }
    }
    __syncthreads();
    if (tid == 0) red_release(&P.cnt[C_CS * CNT_STRIDE]);
    TLREC(0);
    return;
  }

  const int rank = blockIdx.x & 1;
  const int pair = P.role[(blockIdx.x - NHELP) >> 1];
  const int mb = 2 * pair + rank;
  const int cs_ = ((pair >> 3) & 1) * 4 + (pair & 3), tp = (pair >> 4) * 2 + ((pair >> 2) & 1);

#define LOAD_KV(j) do { const int row_ = 128 * (2 * (j) + rank); mbar_expect(BAR(B_RAWF) + 8 * (j), RAWK_BLK + 2048); \
    tma2d(sb + RAWK + (j) * RAWK_BLK, &P.tmK, BAR(B_RAWF) + 8 * (j), 8 * pair, row_ - 8); \
    tma2d(sb + RAWV + (j) * 2048, &P.tmV, BAR(B_RAWF) + 8 * (j), 8 * pair, row_); } while (0)
#define LOAD_Q(j) do { mbar_expect(BAR(B_RAWQF) + 8 * (j), 4096); \
    tma2d(sb + RAWQ + (j) * 4096, &P.tmQ, BAR(B_RAWQF) + 8 * (j), 8 * pair, 128 * (4 * (j) + rank)); \
    tma2d(sb + RAWQ + (j) * 4096 + 2048, &P.tmQ, BAR(B_RAWQF) + 8 * (j), 8 * pair, 128 * (4 * (j) + 2 + rank)); } while (0)

  if (warp == 8) {
    if (elect_one()) {
#pragma unroll
      for (int i = 0; i < 16; i++) mbar_init(BAR(i), 1);
      fence_async_smem();
    }
    __syncwarp();
    nb_arrive(NB_INIT, 384);
    asm volatile("barrier.cluster.arrive.relaxed.aligned;" ::: "memory");
  } else {
    if (warp == 9) {
      if (elect_one()) {
#pragma unroll
        for (int i = 0; i < 5; i++) mbar_init(BAR(B_UF + i), 1);
        mbar_init(BAR(B_RAWDONE), 20); mbar_init(BAR(B_CONVDONE), 16); mbar_init(BAR(B_CS), 1); mbar_init(BAR(B_EXCH), 1);
#pragma unroll
        for (int i = 0; i < 4; i++) mbar_expect(BAR(B_UF + i), 4096);
        mbar_expect(BAR(B_XQF), 16384);
        mbar_expect(BAR(B_EXCH), 16384);
        asm volatile("fence.mbarrier_init.release.cluster;" ::: "memory");
      }
    } else if (warp == 10) {
      if (elect_one()) {
#pragma unroll
        for (int i = 0; i < 3; i++) { mbar_init(BAR(B_WF + i), 1); mbar_init(BAR(B_WE + i), 16); }
#pragma unroll
        for (int i = 0; i < 4; i++) { mbar_init(BAR(B_XF + i), 1); mbar_init(BAR(B_XE + i), 8); }
#pragma unroll
        for (int i = 0; i < 10; i++) mbar_init(BAR(B_SIG + i), i < 2 ? 8 : 4);
        asm volatile("fence.mbarrier_init.release.cluster;" ::: "memory");
        fence_async_smem();
      }
    } else if (warp == 11) {
      if (lane < 8) sts128(sb + UPAD + lane * 16, 0, 0, 0, 0);
      if (lane < 24) { sts128(sb + RED + lane * 16, 0, 0, 0, 0); sts128(sb + RED + RED_WG + lane * 16, 0, 0, 0, 0); }
    } else {
      sts128(sb + KPAD + tid * 16, 0, 0, 0, 0);
    }
    __syncwarp();
    nb_sync(NB_INIT, 384);
    asm volatile("barrier.cluster.arrive.relaxed.aligned;" ::: "memory");
  }

  unsigned zero;
  asm volatile("mov.u32 %0, %%laneid;\nshr.u32 %0, %0, 5;" : "=r"(zero));

  if (warp < 8) {
    asm volatile("setmaxnreg.inc.sync.aligned.u32 224;");
    const unsigned done = ldg_relaxed(&P.cnt[C_DONE * CNT_STRIDE] + zero);
    const uint2 dk = __ldg(reinterpret_cast<const uint2*>(P.ssmD + 4 * mb + zero));
    const int wg = warp >> 2, wq = warp & 3, g = lane >> 2, t = lane & 3;
    const int wtid = tid & 127;
    const uint32_t barsx = mapa(bars, lane & 1);
#define TURN_WAIT() nb_sync(NB_TURN + wg, 256)
#define TURN_PASS() nb_arrive(NB_TURN + (wg ^ 1), 256)
    if (wg == 1) TURN_PASS();
    {
      {
        mbar_wait(BAR(B_QSLAB), 0);
        TLW(56);
        const int r = 2 * warp + (lane >> 4);
        uint4 v[4];
#pragma unroll
        for (int i = 0; i < 4; i++) v[i] = lds128(sb + QSLAB + r * 1024 + (lane & 15) * 16 + i * 256);
        const float piv = blo(__shfl_sync(0xffffffffu, v[0].x, lane & 16));
        float s[4] = {0.f, 0.f, 0.f, 0.f}, q2[4] = {0.f, 0.f, 0.f, 0.f};
#pragma unroll
        for (int i = 0; i < 4; i++) {
          const uint32_t w[4] = {v[i].x, v[i].y, v[i].z, v[i].w};
#pragma unroll
          for (int e = 0; e < 4; e++) {
            const float lo = blo(w[e]) - piv, hi = bhi(w[e]) - piv;
            s[e] += lo + hi; q2[e] = fmaf(lo, lo, fmaf(hi, hi, q2[e]));
          }
        }
        float ss = (s[0] + s[1]) + (s[2] + s[3]), qq = (q2[0] + q2[1]) + (q2[2] + q2[3]);
#pragma unroll
        for (int o = 1; o < 16; o <<= 1) { ss += __shfl_xor_sync(0xffffffffu, ss, o); qq += __shfl_xor_sync(0xffffffffu, qq, o); }
        const float md = ss * (1.f / DM);
        const float var = fmaxf(fmaf(-md, md, qq * (1.f / DM)), 0.f);
        const uint32_t myw = (pack2(md + piv, sqrt_fast(bround(bround(var) + 1e-5f))) & 0x7fffffffu) | ((~done << 24) & 0x80000000u);
        if ((lane & 15) == 0) asm volatile("st.relaxed.gpu.global.u32 [%0], %1;" ::"l"(P.qstat + (r >> 2) * 512 + mb * 4 + (r & 3)), "r"(myw) : "memory");
        TLW(20);
        asm volatile("barrier.cluster.wait.aligned;" ::: "memory");
      }
      const uint32_t red = sb + RED + wg * RED_WG;
      uint32_t ua[3];
#pragma unroll
      for (int i = 0; i < 3; i++) {
        const int W = 8 * wq + g + 2 * t - 8 + i;
        ua[i] = sb + UT + (W >> 3) * 128 + (((wg ^ (W >> 3)) & 3) << 5) + (W & 7) * 4;
      }
      const uint32_t rowo = wtid * 128, sx = (wtid & 7) << 4;
      const int pa = 8 * (lane >> 4) + (lane & 7) + wq;
      const uint32_t rb = red + pa * 128 + (((2 * wq + ((lane >> 3) & 1)) ^ (pa & 7)) << 4);
      float ri[16];
      uint32_t m2[8];
      mbar_wait(BAR(B_KFF), 0);
      filter_block(sb + KRAW + wg * 4096 + wtid * 32, sb + KT + rowo + (((wg * 2) << 4) ^ sx));
      fence_async_smem();
      nb_sync(NB_WG + wg, 128);
#pragma unroll 1
      for (int it = 0; it < 2; it++) {
        const int cl = wg + 2 * it;
        float acc[64];
        uint32_t A0[8][4], A1[8][4];
        const uint32_t d0 = mkdesc(sb + KPAD + cl * 32, 16);
        mbar_wait_cl(BAR(B_UF), 0);
        TLW(3 + cl);
        conv_loadA(A0, ua, 0);
        TURN_WAIT();
        conv_mma<0>(acc, A0, d0);
        TURN_PASS();
        mbar_wait_cl(BAR(B_UF + 1), 0);
        conv_loadA(A1, ua, 4096);
        TURN_WAIT();
        conv_mma<1>(acc, A1, d0);
        TURN_PASS();
        wg_wait<1>();
        mbar_wait_cl(BAR(B_UF + 2), 0);
        conv_loadA(A0, ua, 8192);
        TURN_WAIT();
        conv_mma<2>(acc, A0, d0);
        TURN_PASS();
        if (it == 0) {
          mbar_wait(BAR(B_KFF + 1), 0);
          filter_block(sb + KRAW2 + wg * 4096 + wtid * 32, sb + KT + rowo + (((4 + wg * 2) << 4) ^ sx));
          fence_async_smem();
          mbar_wait(BAR(B_QST), 0);
          const uint32_t tagw = (~done << 24) & 0x80000000u;
          uint4 st[4];
#pragma unroll
          for (int i = 0; i < 4; i++) st[i] = lds128(sb + QST + i * 2048 + wtid * 16);
#pragma unroll 1
          for (int spin = 0; spin < SPIN_LIMIT; spin++) {
            uint32_t bad = 0;
#pragma unroll
            for (int i = 0; i < 4; i++) bad |= (st[i].x ^ tagw) | (st[i].y ^ tagw) | (st[i].z ^ tagw) | (st[i].w ^ tagw);
            if (!__any_sync(0xffffffffu, (int)bad < 0)) break;
#pragma unroll
            for (int i = 0; i < 4; i++) st[i] = ldg_relaxed4(P.qstat + i * 512 + wtid * 4);
          }
#pragma unroll
          for (int i = 0; i < 4; i++) {
            m2[2 * i] = prmt(st[i].x, st[i].y, 0x5410); m2[2 * i + 1] = prmt(st[i].z, st[i].w, 0x5410);
#define RI(w) rcp_fast(__uint_as_float((w) & 0x7fff0000u))
            ri[4 * i] = RI(st[i].x); ri[4 * i + 1] = RI(st[i].y); ri[4 * i + 2] = RI(st[i].z); ri[4 * i + 3] = RI(st[i].w);
#undef RI
          }
          reg_fence<16>(ri);
          TLW(26 + wg);
        }
        wg_wait<0>();
        reg_fence<48>(acc);
#pragma unroll
        for (int j = 0; j < 12; j += 2)
          stsm4t(rb + j * 1024, pack2(acc[4 * j], acc[4 * j + 1]), pack2(acc[4 * j + 2], acc[4 * j + 3]),
                 pack2(acc[4 * j + 4], acc[4 * j + 5]), pack2(acc[4 * j + 6], acc[4 * j + 7]));
        mbar_wait_cl(BAR(B_UF + 3), 0);
        if (it == 0) TLW(16 + wg);
        conv_loadA(A1, ua, 12288);
        conv_mma<3>(acc, A1, d0);
        const uint32_t uo = sb + UT + rowo + (((cl ^ wtid) & 3) << 5);
        const uint4 u0 = lds128(uo), u1 = lds128(uo + 16);
        wg_wait<0>();
        reg_fence<16>(acc + 48);
        TLW(8 + 2 * cl);
#pragma unroll
        for (int j = 12; j < 16; j += 2)
          stsm4t(rb + j * 1024, pack2(acc[4 * j], acc[4 * j + 1]), pack2(acc[4 * j + 2], acc[4 * j + 3]),
                 pack2(acc[4 * j + 4], acc[4 * j + 5]), pack2(acc[4 * j + 6], acc[4 * j + 7]));
        nb_sync(NB_WG + wg, 128);
        uint4 p[8];
#pragma unroll
        for (int i = 0; i < 8; i++) p[i] = lds128(red + rowo + ((i << 4) ^ sx));
        const uint32_t dw = it ? dk.y : dk.x;
        const uint32_t D2 = prmt(dw, dw, wg ? 0x3232 : 0x1010);
#define SUMP(C, H) badd2(badd2(p[H].C, p[2 + H].C), badd2(p[4 + H].C, p[6 + H].C))
        const uint32_t e0 = SUMP(x, 0), o0 = SUMP(x, 1), e1 = SUMP(y, 0), o1 = SUMP(y, 1), e2 = SUMP(z, 0), o2 = SUMP(z, 1), e3 = SUMP(w, 0), o3 = SUMP(w, 1);
#undef SUMP
        uint32_t y[8] = {bfma2(u0.x, D2, prmt(e0, o0, 0x5410)), bfma2(u0.y, D2, prmt(e0, o0, 0x7632)), bfma2(u0.z, D2, prmt(e1, o1, 0x5410)), bfma2(u0.w, D2, prmt(e1, o1, 0x7632)),
                         bfma2(u1.x, D2, prmt(e2, o2, 0x5410)), bfma2(u1.y, D2, prmt(e2, o2, 0x7632)), bfma2(u1.z, D2, prmt(e3, o3, 0x5410)), bfma2(u1.w, D2, prmt(e3, o3, 0x7632))};
#pragma unroll
        for (int i = 0; i < 8; i++) y[i] = pack2(blo(y[i]) * ri[2 * i], bhi(y[i]) * ri[2 * i + 1]);
        mbar_wait_cl(BAR(B_XQF), 0);
        const uint32_t xo = sb + XT + rowo + ((cl << 5) ^ sx);
        const uint4 x0 = lds128(xo), x1 = lds128(xo ^ 16);
        uint4* hp = reinterpret_cast<uint4*>(P.hT + (size_t)(cl * 128 + mb) * S_LEN + 16 * wtid);
        hp[0] = make_uint4(bfma2(bsub2(x0.x, m2[0]), y[0], x0.x), bfma2(bsub2(x0.y, m2[1]), y[1], x0.y), bfma2(bsub2(x0.z, m2[2]), y[2], x0.z), bfma2(bsub2(x0.w, m2[3]), y[3], x0.w));
        hp[1] = make_uint4(bfma2(bsub2(x1.x, m2[4]), y[4], x1.x), bfma2(bsub2(x1.y, m2[5]), y[5], x1.y), bfma2(bsub2(x1.z, m2[6]), y[6], x1.z), bfma2(bsub2(x1.w, m2[7]), y[7], x1.w));
        __syncwarp();
        if (lane == 0) mbar_arrive(BAR(B_SIG) + 8 * it);
        if (lane < 2) mbar_arrive_cl(barsx + 8 * (B_RAWDONE + it));
        TLW(9 + 2 * cl);
#pragma unroll
        for (int i = 0; i < 3; i++) ua[i] ^= 64;
      }
    }

    float accA[64], accB[64];
    const uint32_t dAx = mkdesc(sb + XR + wg * 8192, 16);
    const uint32_t dBw = mkdesc(sb + WR, 8192);
    uint32_t* actp = reinterpret_cast<uint32_t*>(P.act) + (size_t)(2 * tp + rank) * 22 * 4096 + (8 * wg + 2 * wq) * 256 + lane;
    const uint32_t csb = sb + CSM + t * 8;
    RowStat rs;
    float2 cs[16];
    uint32_t ws = 0, wp = 0, wprev = 0;
#define X_WAIT(i, p) mbar_wait(BAR(B_XF) + 8 * (i), p)
#define X_RELEASE(i) do { if (lane == 0) mbar_arrive(BAR(B_XE) + 8 * (i)); } while (0)
#define W_DESC() (dBw + ws * 2048)
#define PREV_DONE() do { mbar_wait(BAR(B_WF) + 8 * ws, wp); wg_wait<0>(); if (lane < 2) mbar_arrive_cl(barsx + 8 * B_WE + 8 * wprev); } while (0)
#define ISSUE(TLI, CALL) do { TURN_WAIT(); TL2(TLI); CALL; TURN_PASS(); wprev = ws; if (++ws == 3) { ws = 0; wp ^= 1; } } while (0)
#define SCHED_FENCE() mbar_wait(BAR(B_RAWDONE), 0)
#define ACT_DONE(p) do { __syncwarp(); if (lane == 0) mbar_arrive(BAR(B_SIG + wg * 5 + 2 + (p))); } while (0)
    {
      const uint32_t hsa = sb + XR + wg * 8192 + ((lane & 7) + 8 * (lane >> 4)) * 128 + (((2 * wq + ((lane >> 3) & 1)) ^ (lane & 7)) << 4);
      float hs[4] = {0.f, 0.f, 0.f, 0.f}, hq[4] = {0.f, 0.f, 0.f, 0.f};
#pragma unroll
      for (int i = 0; i < 64; i++) accA[i] = 0.f;
      mbar_wait(BAR(B_WF), 0);
#pragma unroll 1
      for (int h = 0; h < 2; h++) {
        uint32_t f0[8][4], f1[8][4];
        X_WAIT(2 * h, 0);
        load_frags(f0, hsa + h * 65536);
        ISSUE(8 + 4 * h, mma_unit_rs(accA, f0, W_DESC()));
        X_WAIT(2 * h + 1, 0);
        load_frags(f1, hsa + h * 65536 + 32768);
        row_stats(f1, hs, hq);
        PREV_DONE();
        ISSUE(10 + 4 * h, mma_unit_rs(accA, f1, W_DESC()));
        SCHED_FENCE();
        row_stats(f0, hs, hq);
        if (h == 1) break;
        PREV_DONE();
        ISSUE(16, (mma_unit<0, 8, true>(accB, dAx, W_DESC())));
        PREV_DONE();
        ISSUE(18, (mma_unit<0, 8, false>(accB, dAx + 2048, W_DESC())));
        PREV_DONE();
      }
      mbar_wait(BAR(B_CS), 0);
      load_cs<8>(cs, csb);
      float s0 = hs[0] + hs[2], q0 = hq[0] + hq[2], s1 = hs[1] + hs[3], q1 = hq[1] + hq[3];
#pragma unroll
      for (int o = 1; o < 4; o <<= 1) {
        s0 += __shfl_xor_sync(0xffffffffu, s0, o); q0 += __shfl_xor_sync(0xffffffffu, q0, o);
        s1 += __shfl_xor_sync(0xffffffffu, s1, o); q1 += __shfl_xor_sync(0xffffffffu, q1, o);
      }
      PREV_DONE();
      reg_fence<64>(accA);
      TLW(18 + wg);
      ISSUE(20, (mma_unit<0, 8, false>(accB, dAx + 4096, W_DESC())));
      SCHED_FENCE();
      s0 *= (1.f / DM); s1 *= (1.f / DM);
      const float v0 = fmaxf(fmaf(-s0, s0, q0 * (1.f / DM)), 0.f), v1 = fmaxf(fmaf(-s1, s1, q1 * (1.f / DM)), 0.f);
      rs.m0 = bround(s0); rs.m1 = bround(s1);
      rs.r0 = rcp_fast(bround(sqrt_fast(bround(bround(v0) + 1e-5f)))); rs.r1 = rcp_fast(bround(sqrt_fast(bround(bround(v1) + 1e-5f))));
      rs.h0 = 0.5f * rs.r0; rs.h1 = 0.5f * rs.r1;
    }
    ffn_epi<0, 4, false>(accA, cs, rs, actp + cs_ * 4096, 0, 0);
    PREV_DONE();
    ISSUE(22, (mma_unit<0, 8, false>(accB, dAx + 6144, W_DESC())));
    SCHED_FENCE();
    ffn_epi<4, 8, false>(accA, cs, rs, actp + cs_ * 4096, 0, 0);
    ACT_DONE(0);
    load_cs<8>(cs, csb + 512);
    PREV_DONE();
    reg_fence<64>(accB);
    TLW(22 + wg);
    ISSUE(24, (mma_unit<1, 8, true>(accA, dAx, W_DESC())));
    SCHED_FENCE();
    ffn_epi<0, 5, false>(accB, cs, rs, actp + (8 + cs_) * 4096, 0, 0);
    PREV_DONE();
    X_RELEASE(0);
    ISSUE(26, (mma_unit<1, 8, false>(accA, dAx + 2048, W_DESC())));
    SCHED_FENCE();
    ffn_epi<5, 8, false>(accB, cs, rs, actp + (8 + cs_) * 4096, 0, 0);
    ACT_DONE(1);
    load_cs<6>(cs, csb + 1024);
#pragma unroll 1
    for (int u = 2; u < 4; u++) {
      PREV_DONE();
      X_RELEASE(u - 1);
      ISSUE(24 + 2 * u, (mma_unit<1, 8, false>(accA, dAx + u * 2048, W_DESC())));
    }
    wg_wait<0>();
    if (lane < 2) mbar_arrive_cl(barsx + 8 * B_WE + 8 * wprev);
    X_RELEASE(3);
    reg_fence<56>(accA);
    TLW(24 + wg);
    const uint32_t dAa = mkdesc(sb + XR + wg * 8192, 128);
    const int off3 = 128 + (cs_ < 4 ? 6 * cs_ : 4 + 5 * cs_), ng3 = cs_ < 4 ? 6 : 5;
    ffn_epi<0, 6, true>(accA, cs, rs, actp, off3, ng3);
    ACT_DONE(2);
    mbar_wait(BAR(B_WF) + 8 * ws, wp);
    X_WAIT(0, 1);
    ISSUE(32, (mma_unit<2, 8, true>(accB, dAa, W_DESC())));
#pragma unroll 1
    for (int u = 1; u < 5; u++) {
      wg_wait<0>();
      if (u < 4 && lane < 2) mbar_arrive_cl(barsx + 8 * B_WE + 8 * wprev);
      if (u < 3) X_RELEASE(u - 1);
      mbar_wait(BAR(B_WF) + 8 * ws, wp);
      X_WAIT(u & 3, (u >> 2) ^ 1);
      ISSUE(32 + 2 * u, (mma_unit<2, 8, false>(accB, dAa + (u & 3) * 2048, W_DESC())));
    }
    mbar_wait(BAR(B_WF) + 8 * ws, wp);
    X_WAIT(1, 0);
    if (wg == 0) TURN_WAIT();
    TL2(42);
    if (rank == 0) mma_unit<2, 4, false>(accB, dAa + 2048, W_DESC());
    else mma_unit<2, 2, false>(accB, dAa + 2048, W_DESC());
    uint32_t res[16];
    {
      const uint32_t a = sb + XR + 3 * 16384 + wg * 8192 + ((lane & 7) + 8 * (lane >> 4)) * 128 + (((2 * wq + ((lane >> 3) & 1)) ^ (lane & 7)) << 4);
#pragma unroll
      for (int q = 0; q < 4; q++) ldsm4t(res + 4 * q, a + q * 2048);
    }
    const uint32_t ex = sb + XR + 4 * 16384 + tid * 16;
    const uint32_t rex = mapa(ex, rank ^ 1), rbar = mapa(BAR(B_EXCH), rank ^ 1);
    wg_wait<0>();
    reg_fence<64>(accB);
    TLW(32 + wg);
    {
#pragma unroll
      for (int q = 0; q < 4; q++) {
        uint32_t o[4];
#pragma unroll
        for (int e = 0; e < 4; e++) o[e] = pack2(accB[32 + 8 * q + 2 * e], accB[32 + 8 * q + 2 * e + 1]);
        st_async4(rex + q * 4096, o, rbar);
      }
#pragma unroll
      for (int j = 0; j < 16; j++) { accB[2 * j] += blo(res[j]); accB[2 * j + 1] += bhi(res[j]); }
      const uint32_t stg = sb + XR + 5 * 16384 + wg * 8192;
      const int i = lane & 7, mat = lane >> 3;
      const uint32_t rowa = stg + (16 * wq + 8 * (mat & 1) + i) * 128;
      mbar_wait_cl(BAR(B_EXCH), 0);
      TLW(1 + wg);
#pragma unroll
      for (int q = 0; q < 4; q++) {
        const uint4 v = lds128(ex + q * 4096);
        stsm4(rowa + (((2 * q + (mat >> 1)) ^ i) << 4), pack2(accB[8 * q] + blo(v.x), accB[8 * q + 1] + bhi(v.x)), pack2(accB[8 * q + 2] + blo(v.y), accB[8 * q + 3] + bhi(v.y)),
              pack2(accB[8 * q + 4] + blo(v.z), accB[8 * q + 5] + bhi(v.z)), pack2(accB[8 * q + 6] + blo(v.w), accB[8 * q + 7] + bhi(v.w)));
      }
      fence_async_smem();
      nb_sync(NB_WG + wg, 128);
      if (wq == 0 && elect_one()) {
        asm volatile("cp.async.bulk.tensor.2d.global.shared::cta.bulk_group [%0, {%2,%3}], [%1];" ::"l"(&P.tmOut), "r"(stg),
                     "r"(128 * (cs_ >> 1) + 64 * rank), "r"(128 * (2 * tp + (cs_ & 1)) + 64 * wg) : "memory");
        asm volatile("cp.async.bulk.commit_group;" ::: "memory");
        if (wg == 0) asm volatile("red.relaxed.gpu.global.add.u32 [%0], 1;" ::"l"(&P.cnt[C_DONE * CNT_STRIDE]) : "memory");
        asm volatile("cp.async.bulk.wait_group.read 0;" ::: "memory");
        TLONE(34 + wg);
      }
    }
  } else {
    asm volatile("setmaxnreg.dec.sync.aligned.u32 56;");
    if (warp == 8 && elect_one()) {
      mbar_expect(BAR(B_QSLAB), 16384);
      bulk_ld(sb + QSLAB, P.q + (size_t)mb * 16 * DM, 16384, BAR(B_QSLAB));
      TLONE(39);
#pragma unroll 1
      for (int j = 0; j < AHEAD; j++) LOAD_KV(j);
      mbar_expect(BAR(B_KFF), 8192);
      bulk_ld(sb + KRAW, P.ssmk + (size_t)(4 * mb) * S_LEN, 8192, BAR(B_KFF));
      TLONE(38);
    }
    __syncwarp();
    const uint2 small = __ldg(reinterpret_cast<const uint2*>(P.shiftk + (8 * pair + (lane >> 2)) * 4));
    const unsigned done = ldg_relaxed(&P.cnt[C_DONE * CNT_STRIDE] + zero);
    {
      trap_if(sb & 1023u);
      asm volatile("barrier.cluster.wait.aligned;" ::: "memory");
      const int wq = warp & 3, g = lane >> 2, t = lane & 3;
      const uint32_t lro = (32 * wq + 8 * ((lane & 7) >> 1) + 2 * (lane >> 3) + (lane & 1)) * 16;
      const int nl = 8 * rank + 2 * wq + (t >> 1);
      const uint32_t rsb = mapa(sb, g >> 2);
      const uint32_t dU = rsb + UT + nl * 128 + (((g ^ nl) & 3) << 5) + (t & 1) * 16;
      const uint32_t w0 = prmt(small.x, small.x, 0x1010), w1 = prmt(small.x, small.x, 0x3232), w2 = prmt(small.y, small.y, 0x1010), w3 = prmt(small.y, small.y, 0x3232);
#pragma unroll 1
      for (int j = 0; j < 8; j++) {
        mbar_wait_aux(BAR(B_RAWF) + 8 * j, 0);
        uint32_t k[6], vv[4], s1[5];
        const uint32_t ka = sb + RAWK + 128 + j * RAWK_BLK + lro;
        ldsm2t(k, ka - 64); ldsm4t(k + 2, ka);
        ldsm4t(vv, sb + RAWV + j * 2048 + lro);
        if (wq == (j & 3) && elect_one()) {
          if (j + AHEAD < 8) LOAD_KV(j + AHEAD);
          if (j >= 4) LOAD_Q(j - 4);
          if (j == 2) {
            mbar_expect(BAR(B_KFF + 1), 8192);
            bulk_ld(sb + KRAW2, P.ssmk + (size_t)(4 * mb + 2) * S_LEN, 8192, BAR(B_KFF + 1));
          }
          if (j == QST_POS) {
            mbar_expect(BAR(B_QST), 8192);
            bulk_ld(sb + QST, P.qstat, 8192, BAR(B_QST));
          }
        }
#pragma unroll
        for (int i = 0; i < 5; i++) s1[i] = prmt(k[i], k[i + 1], 0x5432);
#pragma unroll
        for (int i = 0; i < 4; i++) vv[i] = bmul2(bfma2(k[i + 2], w0, bfma2(s1[i + 1], w1, bfma2(k[i + 1], w2, bmul2(s1[i], w3)))), vv[i]);
        st_async4(dU + j * 2048, vv, rsb + BARS + 8 * B_UF + 8 * (j >> 1));
      }
      TLW(36);
      const uint32_t dX = rsb + XT + nl * 128 + ((((g & 3) * 2 + (t & 1)) ^ (nl & 7)) << 4);
      uint32_t x[8][4];
#pragma unroll
      for (int s = 0; s < 4; s++) {
        mbar_wait_aux(BAR(B_RAWQF + s), 0);
        TLW(28 + s);
        ldsm4t(x[2 * s], sb + RAWQ + s * 4096 + lro);
        ldsm4t(x[2 * s + 1], sb + RAWQ + s * 4096 + 2048 + lro);
        if (s > 0) {
          st_async4(dX + s * 4096 - 4096, x[2 * s - 2], rsb + BARS + 8 * B_XQF);
          st_async4(dX + s * 4096 - 2048, x[2 * s - 1], rsb + BARS + 8 * B_XQF);
        }
      }
      st_async4(dX + 3 * 4096, x[6], rsb + BARS + 8 * B_XQF);
      st_async4(dX + 3 * 4096 + 2048, x[7], rsb + BARS + 8 * B_XQF);
      __syncwarp();
      if (lane == 0) mbar_arrive(BAR(B_RAWDONE));
      TLW(52);
    }
    const unsigned ep = (done >> 7) + 1;
    if (warp == 8) {
      if (elect_one()) {
        const int col3 = 1024 + 8 * (cs_ < 4 ? 6 * cs_ : 4 + 5 * cs_);
        const CUtensorMap* tw = rank ? &P.tmWu : &P.tmWg;
        uint32_t slot = 0, par = 1;
#pragma unroll 1
        for (int u = 0; u < 18; u++) {
          if (u == 1) mbar_wait_aux(BAR(B_CONVDONE), 0);
          if (u == 4) l2_prefetch(P.wd + (size_t)mb * 5504, 11008);
          mbar_wait_aux(BAR(B_WE) + 8 * slot, par);
          const uint32_t fb = BAR(B_WF) + 8 * slot, dst = sb + WR + slot * 32768;
          mbar_expect(fb, u < 17 ? 32768 : 16384);
          if (u < 12) {
            const int col = u < 8 ? 64 * (4 * (u & 2) + cs_) : col3;
            const int q = u < 8 ? (u & 1) + ((u >> 1) & 2) : u - 8;
            tma3d_mc(dst + rank * 8192, tw, fb, col, q, 0);
            tma3d_mc(dst + 16384 + rank * 8192, tw, fb, col, q, 64);
          } else {
            const int k0 = 64 * (4 * (u - 12) + rank), c0 = 128 * (cs_ >> 1);
            tma2d(dst, &P.tmWd, fb, c0 + 64 * rank, k0);
            tma2d(dst + 8192, &P.tmWd, fb, c0 + 64 * (rank ^ 1), k0);
            if (u < 17) {
              tma2d(dst + 16384, &P.tmWd, fb, c0 + 64 * rank, k0 + 128);
              tma2d(dst + 24576, &P.tmWd, fb, c0 + 64 * (rank ^ 1), k0 + 128);
            }
          }
          if (++slot == 3) { slot = 0; par ^= 1; }
        }
      }
    } else if (warp == 9) {
      if (elect_one()) {
        const int s0 = 128 * (2 * tp + rank);
#pragma unroll 1
        for (int q = 0; q < 4; q++) {
          if (!(q & 1)) {
            mbar_wait_aux(BAR(B_RAWDONE) + 4 * q, 0);
            poll_cnt(&P.cnt[(C_H + (q >> 1)) * CNT_STRIDE], ep * 128);
            fence_async();
          }
          mbar_expect(BAR(B_XF) + 8 * q, 32768);
#pragma unroll
          for (int i = 0; i < 4; i++) tma2d(sb + XR + q * 32768 + i * 8192, &P.tmH, BAR(B_XF) + 8 * q, s0 + 64 * (i & 1), 128 * q + 64 * (i >> 1));
          TLONE(40 + q);
        }
        const int tile2 = 2 * tp + (cs_ & 1);
        const __nv_bfloat16* src = P.act + ((size_t)tile2 * 22 + rank) * 8192;
#pragma unroll 1
        for (int u = 0; u < 6; u++) {
          const uint32_t slot = u & 3, fb = BAR(B_XF) + 8 * slot, dst = sb + XR + slot * 32768;
          if (!(u & 1)) { poll_cnt(&P.cnt[(C_A + tile2 * 3 + (u >> 1)) * CNT_STRIDE], ep * 16); fence_async(); TLONE(48 + (u >> 1)); }
          mbar_wait_aux(BAR(B_XE) + 8 * slot, u >> 2);
          mbar_expect(fb, 32768);
          bulk_ld(dst, src + u * 32768, 16384, fb);
          if (u < 5) bulk_ld(dst + 16384, src + u * 32768 + 16384, 16384, fb);
          else {
            const int g0 = 32 * (cs_ >> 1) + 16 * rank;
            tma3d(dst + 16384, &P.tmR, fb, 128 * tile2, 0, g0);
            tma3d(dst + 24576, &P.tmR, fb, 128 * tile2 + 64, 0, g0);
          }
        }
      }
    } else {
      const int wg = warp - 10;
#pragma unroll 1
      for (int ev = 1; ev < 5; ev++) {
        if (ev == 2 && wg == 0) {
          poll_cnt(&P.cnt[C_CS * CNT_STRIDE], ep * 4);
          const int col3 = 1024 + 8 * (cs_ < 4 ? 6 * cs_ : 4 + 5 * cs_);
          float2 a[3][8];
#pragma unroll
          for (int p = 0; p < 2; p++)
#pragma unroll
            for (int i = 0; i < 8; i++) a[p][i] = __ldcg(reinterpret_cast<const float2*>(P.colsum + i * 1408 + 512 * p + 64 * cs_ + 2 * lane));
#pragma unroll
          for (int p = 0; p < 3; p++) {
            if (p == 1) {
#pragma unroll
              for (int i = 0; i < 8; i++) a[2][i] = __ldcg(reinterpret_cast<const float2*>(P.colsum + i * 1408 + col3 + 2 * lane));
            }
            sts64f(sb + CSM + p * 512 + lane * 8, (a[p][0].x + a[p][1].x) + (a[p][2].x + a[p][3].x), (a[p][0].y + a[p][1].y) + (a[p][2].y + a[p][3].y));
            sts64f(sb + CSM + p * 512 + 256 + lane * 8, (a[p][4].x + a[p][5].x) + (a[p][6].x + a[p][7].x), (a[p][4].y + a[p][5].y) + (a[p][6].y + a[p][7].y));
          }
          __syncwarp();
          if (lane == 0) mbar_arrive(BAR(B_CS));
          TLREC(58);
        }
        mbar_wait_aux(ev < 2 ? BAR(B_SIG + wg) : BAR(B_SIG + wg * 5) + 8 * ev, 0);
        if (lane == 0) red_release(&P.cnt[(ev < 2 ? C_H + wg : C_A + (2 * tp + rank) * 3 + ev - 2) * CNT_STRIDE]);
        __syncwarp();
      }
    }
  }
}

typedef CUresult (*EncFn)(CUtensorMap*, CUtensorMapDataType, cuuint32_t, void*, const cuuint64_t*, const cuuint64_t*, const cuuint32_t*,
                          const cuuint32_t*, CUtensorMapInterleave, CUtensorMapSwizzle, CUtensorMapL2promotion, CUtensorMapFloatOOBfill);

void enc(EncFn fn, CUtensorMap* tm, const void* ptr, int rank, const cuuint64_t* gd, const cuuint64_t* gs, const cuuint32_t* bd, bool sw) {
  cuuint32_t es[3] = {1, 1, 1};
  fn(tm, CU_TENSOR_MAP_DATA_TYPE_BFLOAT16, rank, const_cast<void*>(ptr), gd, gs, bd, es, CU_TENSOR_MAP_INTERLEAVE_NONE,
     sw ? CU_TENSOR_MAP_SWIZZLE_128B : CU_TENSOR_MAP_SWIZZLE_NONE, CU_TENSOR_MAP_L2_PROMOTION_L2_128B, CU_TENSOR_MAP_FLOAT_OOB_FILL_NONE);
}

}

extern "C" void kernel_launch(void* const* d_in, const int* in_sizes, int n_in, void* d_out, int out_size) {
  (void)in_sizes; (void)n_in; (void)out_size;
  static EncFn fn = nullptr;
  static void *hT = nullptr, *act = nullptr, *qstat = nullptr, *cnt = nullptr, *colsum = nullptr;
  if (!fn) {
    void* f = nullptr;
    cudaDriverEntryPointQueryResult qr;
    cudaGetDriverEntryPoint("cuTensorMapEncodeTiled", &f, cudaEnableDefault, &qr);
    fn = (EncFn)f;
    cudaGetSymbolAddress(&hT, g_hT); cudaGetSymbolAddress(&act, g_act); cudaGetSymbolAddress(&qstat, g_qstat);
    cudaGetSymbolAddress(&cnt, g_cnt); cudaGetSymbolAddress(&colsum, g_colsum);
    cudaFuncSetAttribute(fused_kernel, cudaFuncAttributeMaxDynamicSharedMemorySize, SMEM_TOTAL);
  }
  Params P;
  P.q = (const __nv_bfloat16*)d_in[0];
  P.hT = (__nv_bfloat16*)hT; P.act = (__nv_bfloat16*)act; P.qstat = (unsigned*)qstat; P.cnt = (unsigned*)cnt; P.colsum = (float*)colsum;
  P.shiftk = (const __nv_bfloat16*)d_in[3]; P.ssmk = (const __nv_bfloat16*)d_in[4]; P.ssmD = (const __nv_bfloat16*)d_in[5];
  P.wd = (const __nv_bfloat16*)d_in[9];
  {
    cuuint64_t gd[2] = {DM, S_LEN}, gs[1] = {DM * 2};
    cuuint32_t bk[2] = {8, 136}, bv[2] = {8, 128}, bo[2] = {64, 64};
    enc(fn, &P.tmK, d_in[1], 2, gd, gs, bk, false);
    enc(fn, &P.tmV, d_in[2], 2, gd, gs, bv, false);
    enc(fn, &P.tmQ, P.q, 2, gd, gs, bv, false);
    enc(fn, &P.tmOut, d_out, 2, gd, gs, bo, true);
  }
  {
    cuuint64_t gd[3] = {FF, 4, 128}, gs[2] = {FF * 2, FF * 8};
    cuuint32_t bd[3] = {64, 1, 64};
    enc(fn, &P.tmWg, d_in[7], 3, gd, gs, bd, true);
    enc(fn, &P.tmWu, d_in[8], 3, gd, gs, bd, true);
  }
  {
    cuuint64_t gd[2] = {DM, FF}, gs[1] = {DM * 2};
    cuuint32_t bd[2] = {64, 64};
    enc(fn, &P.tmWd, P.wd, 2, gd, gs, bd, true);
  }
  {
    cuuint64_t gd[2] = {S_LEN, DM}, gs[1] = {S_LEN * 2};
    cuuint32_t bd[2] = {64, 64};
    enc(fn, &P.tmH, hT, 2, gd, gs, bd, true);
  }
  {
    cuuint64_t gd[3] = {S_LEN, 4, 128}, gs[2] = {128 * S_LEN * 2, S_LEN * 2};
    cuuint32_t bd[3] = {64, 4, 16};
    enc(fn, &P.tmR, hT, 3, gd, gs, bd, true);
  }
  {
    int cnt[8] = {0, 0, 0, 0, 0, 0, 0, 0};
    for (int pass = 0; pass < 2; pass++)
      for (int b = 0; b < NMAIN / 2; b++) {
        const int tp = b - 2;
        if ((pass == 0) != (tp >= 0 && tp < 32)) continue;
        const int g = tp < 0 ? 0 : tp < 32 ? tp % 8 : tp < 60 ? 1 + (tp - 32) % 7 : 0;
        const int i = cnt[g]++;
        P.role[b] = (unsigned char)(g * 8 + i);
      }
  }
  fused_kernel<<<NHELP + NMAIN, 384, SMEM_TOTAL, cudaStreamPerThread>>>(P);
}
```

```cpp
#include <cuda_runtime.h>
#include <cuda_bf16.h>
#include <cuda.h>
#include <stdint.h>

namespace {

constexpr int S_LEN = 2048, DM = 512, FF = 1376;
constexpr int NHELP = 4, NMAIN = 128;

constexpr uint32_t XR = 0, WR = 131072, MISC = 229376, SMEM_TOTAL = 232448;
constexpr uint32_t RAWK = 0, RAWK_BLK = 2176, RAWV = 17408, KRAW2 = 40960;
constexpr uint32_t KPAD = 65536, KT = KPAD + 4096, XT = KT + 16384, UPAD = XT + 16384, UT = UPAD + 256, DUMMY = UT + 16384, RPK = DUMMY + 128;
constexpr uint32_t RAWQ = 49152, QSLAB = WR + 2 * 16384, QST = WR + 3 * 16384, RED = WR + 4 * 16384, RED_WG = 16384, KRAW = RED + 1024;
constexpr uint32_t CSM = MISC, BARS = MISC + 2048, SMALL = BARS + 640;
constexpr int B_RAWF = 0  , B_RAWQF = 8  , B_KFF = 12  , B_QSLAB = 14, B_QST = 15, B_UF = 16  , B_XQF = 20,
              B_RAWDONE = 21, B_CONVDONE = 22, B_CS = 23, B_KT2 = 24, B_WF = 25  , B_WE = 28  ,
              B_XF = 31  , B_H1 = 35, B_A16 = 36, B_X0B = 37, B_SIG = 39  , B_EXCH = 44  , B_PFREE = 46  , B_SMALL = 48, B_PUB = 49, B_RPK = 50,
              B_AF = 51  , B_GF = 58  , B_UD = 64  ;
constexpr int NB_WG = 1  , NB_INIT = 3, NB_TURN = 5  , NB_GATE = 7  ;

struct __align__(64) Params {
  CUtensorMap tmK, tmV, tmQ, tmWg, tmWu, tmWd, tmH, tmR, tmG3, tmU3;
  const __nv_bfloat16 *q, *shiftk, *ssmk, *ssmD, *wd;
  __nv_bfloat16 *hT, *act, *out;
  unsigned *cnt, *colsum;
  uint4 *qstat, *hstat, *w3;
  unsigned zero, hi_sw, hi_no, hi_w3;
};

__device__ __align__(1024) __nv_bfloat16 g_hT[DM * S_LEN];
__device__ __align__(1024) __nv_bfloat16 g_act[16 * 22 * 8192];
__device__ __align__(128) uint4 g_qstat[S_LEN / 2];
__device__ __align__(128) uint4 g_hstat[S_LEN * 4];
__device__ __align__(1024) uint4 g_w3[8 * 64 * 12 * 8];
__device__ __align__(128) unsigned g_colsum[4 * 704];
constexpr int CNT_STRIDE = 64;
constexpr int C_H = 0, C_A = 8, C_CS = 56, C_DONE = 57;
__device__ __align__(256) unsigned g_cnt[64 * CNT_STRIDE];
#define TLREC(i) do { } while (0)
#define TLD(i) do { } while (0)
#define TLONE(i) do { } while (0)
#define TLW(i) do { } while (0)
#define TL2(i) do { } while (0)

#define TLC(i) do { } while (0)

__device__ __forceinline__ uint32_t smem_u32(const void* p) { return (uint32_t)__cvta_generic_to_shared(p); }
__device__ __forceinline__ void mbar_init(uint32_t bar, uint32_t cnt) { asm volatile("mbarrier.init.shared::cta.b64 [%0], %1;" ::"r"(bar), "r"(cnt) : "memory"); }
__device__ __forceinline__ void mbar_expect(uint32_t bar, uint32_t bytes) { asm volatile("mbarrier.arrive.expect_tx.shared::cta.b64 _, [%0], %1;" ::"r"(bar), "r"(bytes) : "memory"); }
__device__ __forceinline__ void mbar_arrive(uint32_t bar) { asm volatile("mbarrier.arrive.shared::cta.b64 _, [%0];" ::"r"(bar) : "memory"); }
#define SPIN_LIMIT_STR "2000000"
constexpr int SPIN_LIMIT = 4000000;
__device__ __forceinline__ void mbar_wait_aux(uint32_t bar, uint32_t parity) {
  asm volatile("{\n.reg .pred p;\n.reg .u32 c;\nmov.u32 c, 0;\nLW_%=:\n"
               "mbarrier.try_wait.parity.shared::cta.b64 p, [%0], %1;\n@p bra LD_%=;\n"
               "add.u32 c, c, 1;\nsetp.gt.u32 p, c, " SPIN_LIMIT_STR ";\n@p trap;\nbra LW_%=;\nLD_%=:\n}" ::"r"(bar), "r"(parity) : "memory");
}
__device__ __forceinline__ void mbar_wait(uint32_t bar, uint32_t parity) {
  asm volatile("{\n.reg .pred p;\n.reg .u32 c;\nmov.u32 c, 0;\nLW_%=:\n"
               "mbarrier.try_wait.parity.shared::cta.b64 p, [%0], %1;\n@p bra LD_%=;\n"
               "add.u32 c, c, 1;\nsetp.le.u32 p, c, 4000000;\n@p bra LW_%=;\nLD_%=:\n}" ::"r"(bar), "r"(parity) : "memory");
}
__device__ __forceinline__ void mbar_wait_cl(uint32_t bar, uint32_t parity) {
  asm volatile("{\n.reg .pred p;\n.reg .u32 c;\nmov.u32 c, 0;\nLW_%=:\n"
               "mbarrier.try_wait.parity.acquire.cluster.shared::cta.b64 p, [%0], %1;\n@p bra LD_%=;\n"
               "add.u32 c, c, 1;\nsetp.le.u32 p, c, 4000000;\n@p bra LW_%=;\nLD_%=:\n}" ::"r"(bar), "r"(parity) : "memory");
}
__device__ __forceinline__ bool mbar_test(uint32_t bar, uint32_t parity) {
  uint32_t ok;
  asm volatile("{\n.reg .pred p;\nmbarrier.test_wait.parity.shared::cta.b64 p, [%1], %2;\nselp.u32 %0, 1, 0, p;\n}" : "=r"(ok) : "r"(bar), "r"(parity) : "memory");
  return __all_sync(0xffffffffu, ok);
}
__device__ __forceinline__ void poll_cnt(const unsigned* p, unsigned target) {
  asm volatile("{\n.reg .pred p;\n.reg .u32 c, v;\n.reg .s32 d;\nmov.u32 c, 0;\nLW_%=:\n"
               "ld.acquire.gpu.global.u32 v, [%0];\nsub.s32 d, v, %1;\nsetp.ge.s32 p, d, 0;\n@p bra LD_%=;\n"
               "add.u32 c, c, 1;\nsetp.gt.u32 p, c, " SPIN_LIMIT_STR ";\n@p trap;\nbra LW_%=;\nLD_%=:\n}" ::"l"(p), "r"(target) : "memory");
}
__device__ __forceinline__ void trap_if(bool c) { asm volatile("{\n.reg .pred p;\nsetp.ne.u32 p, %0, 0;\n@p trap;\n}" ::"r"((uint32_t)c)); }
__device__ __forceinline__ void red_release(unsigned* p) {
  asm volatile("fence.proxy.async;\nred.relaxed.gpu.global.add.u32 [%0], 1;" ::"l"(p) : "memory");
}
__device__ __forceinline__ void fence_async() { asm volatile("fence.proxy.async.global;" ::: "memory"); }
__device__ __forceinline__ void fence_async_smem() { asm volatile("fence.proxy.async.shared::cta;" ::: "memory"); }
__device__ __forceinline__ void nb_sync(int id, int n) { asm volatile("bar.sync %0, %1;" ::"r"(id), "r"(n) : "memory"); }
__device__ __forceinline__ void nb_arrive(int id, int n) { asm volatile("bar.arrive %0, %1;" ::"r"(id), "r"(n) : "memory"); }
__device__ __forceinline__ bool elect_one() {
  uint32_t p;
  asm volatile("{\n.reg .pred P;\nelect.sync _|P, 0xffffffff;\nselp.b32 %0, 1, 0, P;\n}" : "=r"(p));
  return p != 0;
}
__device__ __forceinline__ void stsm4t(uint32_t addr, uint32_t a, uint32_t b, uint32_t c, uint32_t d) {
  asm volatile("stmatrix.sync.aligned.m8n8.x4.trans.shared.b16 [%0], {%1,%2,%3,%4};" ::"r"(addr), "r"(a), "r"(b), "r"(c), "r"(d) : "memory");
}
__device__ __forceinline__ uint4 ldg_relaxed4(const void* p) {
  uint4 v;
  asm volatile("ld.relaxed.gpu.global.v4.u32 {%0,%1,%2,%3}, [%4];" : "=r"(v.x), "=r"(v.y), "=r"(v.z), "=r"(v.w) : "l"(p) : "memory");
  return v;
}
__device__ __forceinline__ unsigned ldg_relaxed(const unsigned* p) {
  unsigned v;
  asm volatile("ld.relaxed.gpu.global.u32 %0, [%1];" : "=r"(v) : "l"(p) : "memory");
  return v;
}
__device__ __forceinline__ uint32_t mapa(uint32_t a, uint32_t r) { uint32_t o; asm("mapa.shared::cluster.u32 %0, %1, %2;" : "=r"(o) : "r"(a), "r"(r)); return o; }
__device__ __forceinline__ void tma2d(uint32_t dst, const CUtensorMap* tm, uint32_t bar, int c0, int c1) {
  asm volatile("cp.async.bulk.tensor.2d.shared::cluster.global.mbarrier::complete_tx::bytes [%0], [%1, {%3,%4}], [%2];" ::"r"(dst), "l"(tm), "r"(bar), "r"(c0), "r"(c1) : "memory");
}
__device__ __forceinline__ void tma3d(uint32_t dst, const CUtensorMap* tm, uint32_t bar, int c0, int c1, int c2) {
  asm volatile("cp.async.bulk.tensor.3d.shared::cluster.global.mbarrier::complete_tx::bytes [%0], [%1, {%3,%4,%5}], [%2];" ::"r"(dst), "l"(tm), "r"(bar), "r"(c0), "r"(c1), "r"(c2) : "memory");
}
__device__ __forceinline__ void tma3d_mc(uint32_t dst, const CUtensorMap* tm, uint32_t bar, int c0, int c1, int c2) {
  asm volatile("cp.async.bulk.tensor.3d.shared::cluster.global.mbarrier::complete_tx::bytes.multicast::cluster [%0], [%1, {%3,%4,%5}], [%2], %6;" ::"r"(dst), "l"(tm), "r"(bar), "r"(c0), "r"(c1), "r"(c2), "h"((uint16_t)3) : "memory");
}
__device__ __forceinline__ void mbar_arrive_cl(uint32_t bar) { asm volatile("mbarrier.arrive.shared::cluster.b64 _, [%0];" ::"r"(bar) : "memory"); }
__device__ __forceinline__ uint32_t bsub2(uint32_t a, uint32_t b) { uint32_t d; asm("sub.rn.bf16x2 %0, %1, %2;" : "=r"(d) : "r"(a), "r"(b)); return d; }
__device__ __forceinline__ uint32_t bfma2(uint32_t a, uint32_t b, uint32_t c) { uint32_t d; asm("fma.rn.bf16x2 %0, %1, %2, %3;" : "=r"(d) : "r"(a), "r"(b), "r"(c)); return d; }
__device__ __forceinline__ void bulk_ld(uint32_t dst, const void* src, uint32_t bytes, uint32_t bar) {
  asm volatile("cp.async.bulk.shared::cluster.global.mbarrier::complete_tx::bytes [%0], [%1], %2, [%3];" ::"r"(dst), "l"(src), "r"(bytes), "r"(bar) : "memory");
}
__device__ __forceinline__ void l2_prefetch(const void* src, uint32_t bytes) { asm volatile("cp.async.bulk.prefetch.L2.global [%0], %1;" ::"l"(src), "r"(bytes) : "memory"); }
__device__ __forceinline__ void ldsm4t(uint32_t* r, uint32_t addr) {
  asm volatile("ldmatrix.sync.aligned.m8n8.x4.trans.shared.b16 {%0,%1,%2,%3}, [%4];" : "=r"(r[0]), "=r"(r[1]), "=r"(r[2]), "=r"(r[3]) : "r"(addr) : "memory");
}
__device__ __forceinline__ void lds64(uint32_t& x, uint32_t& y, uint32_t a) { asm volatile("ld.shared.v2.b32 {%0,%1}, [%2];" : "=r"(x), "=r"(y) : "r"(a) : "memory"); }
__device__ __forceinline__ void stsm4(uint32_t addr, uint32_t a, uint32_t b, uint32_t c, uint32_t d) {
  asm volatile("stmatrix.sync.aligned.m8n8.x4.shared.b16 [%0], {%1,%2,%3,%4};" ::"r"(addr), "r"(a), "r"(b), "r"(c), "r"(d) : "memory");
}
__device__ __forceinline__ uint32_t lds32(uint32_t a) { uint32_t v; asm volatile("ld.shared.b32 %0, [%1];" : "=r"(v) : "r"(a) : "memory"); return v; }
__device__ __forceinline__ uint4 lds128(uint32_t a) { uint4 v; asm volatile("ld.shared.v4.b32 {%0,%1,%2,%3}, [%4];" : "=r"(v.x), "=r"(v.y), "=r"(v.z), "=r"(v.w) : "r"(a) : "memory"); return v; }
__device__ __forceinline__ void sts32(uint32_t a, uint32_t x) { asm volatile("st.shared.b32 [%0], %1;" ::"r"(a), "r"(x) : "memory"); }
__device__ __forceinline__ void sts128(uint32_t a, uint32_t x, uint32_t y, uint32_t z, uint32_t w) { asm volatile("st.shared.v4.b32 [%0], {%1,%2,%3,%4};" ::"r"(a), "r"(x), "r"(y), "r"(z), "r"(w) : "memory"); }
__device__ __forceinline__ void st_async4(uint32_t a, const uint32_t* v, uint32_t bar) {
  asm volatile("st.async.weak.shared::cluster.mbarrier::complete_tx::bytes.v4.b32 [%0], {%1,%2,%3,%4}, [%5];" ::"r"(a), "r"(v[0]), "r"(v[1]), "r"(v[2]), "r"(v[3]), "r"(bar) : "memory");
}
__device__ __forceinline__ uint32_t prmt(uint32_t a, uint32_t b, uint32_t s) { uint32_t d; asm("prmt.b32 %0, %1, %2, %3;" : "=r"(d) : "r"(a), "r"(b), "r"(s)); return d; }
__device__ __forceinline__ uint32_t bmul2(uint32_t a, uint32_t b) { uint32_t d; asm("mul.rn.bf16x2 %0, %1, %2;" : "=r"(d) : "r"(a), "r"(b)); return d; }
__device__ __forceinline__ uint32_t badd2(uint32_t a, uint32_t b) { uint32_t d; asm("add.rn.bf16x2 %0, %1, %2;" : "=r"(d) : "r"(a), "r"(b)); return d; }
__device__ __forceinline__ uint32_t pack2(float lo, float hi) { uint32_t d; asm("cvt.rn.bf16x2.f32 %0, %1, %2;" : "=r"(d) : "f"(hi), "f"(lo)); return d; }
__device__ __forceinline__ float blo(uint32_t w) { return __uint_as_float(w << 16); }
__device__ __forceinline__ float bhi(uint32_t w) { return __uint_as_float(w & 0xffff0000u); }
__device__ __forceinline__ float tanh_fast(float x) { float y; asm("tanh.approx.f32 %0, %1;" : "=f"(y) : "f"(x)); return y; }
__device__ __forceinline__ float sqrt_fast(float x) { float y; asm("sqrt.approx.ftz.f32 %0, %1;" : "=f"(y) : "f"(x)); return y; }
__device__ __forceinline__ float rcp_fast(float x) { float y; asm("rcp.approx.ftz.f32 %0, %1;" : "=f"(y) : "f"(x)); return y; }
__device__ __forceinline__ uint32_t mkdesc(uint32_t addr, uint32_t lbo) { return ((addr & 0x3FFFF) >> 4) | ((lbo >> 4) << 16); }
__device__ __forceinline__ uint64_t udesc(uint32_t lo, uint32_t hi) {
  uint32_t u;
  asm volatile("redux.sync.or.b32 %0, %1, 0xffffffff;" : "=r"(u) : "r"(lo));
  return (uint64_t)u | ((uint64_t)hi << 32);
}
__device__ __forceinline__ void wg_fence() { asm volatile("wgmma.fence.sync.aligned;" ::: "memory"); }
__device__ __forceinline__ void wg_commit() { asm volatile("wgmma.commit_group.sync.aligned;" ::: "memory"); }
template <int N> __device__ __forceinline__ void wg_wait() { asm volatile("wgmma.wait_group.sync.aligned %0;" ::"n"(N) : "memory"); }
template <int N> __device__ __forceinline__ void reg_fence(float* d) {
#pragma unroll
  for (int i = 0; i < N; i++) asm volatile("" : "+f"(d[i])::"memory");
}

__device__ __forceinline__ void wg_conv0(float* d, const uint32_t* a, uint64_t db) {
  asm volatile("wgmma.mma_async.sync.aligned.m64n32k16.f32.bf16.bf16 {%0,%1,%2,%3,%4,%5,%6,%7,%8,%9,%10,%11,%12,%13,%14,%15}, {%16,%17,%18,%19}, %20, 0, 1, 1, 0;"
    : "=f"(d[0]),"=f"(d[1]),"=f"(d[2]),"=f"(d[3]),"=f"(d[4]),"=f"(d[5]),"=f"(d[6]),"=f"(d[7]),"=f"(d[8]),"=f"(d[9]),"=f"(d[10]),"=f"(d[11]),"=f"(d[12]),"=f"(d[13]),"=f"(d[14]),"=f"(d[15])
    : "r"(a[0]),"r"(a[1]),"r"(a[2]),"r"(a[3]),"l"(db));
}
__device__ __forceinline__ void wg_conv(float* d, const uint32_t* a, uint64_t db) {
  asm volatile("wgmma.mma_async.sync.aligned.m64n32k16.f32.bf16.bf16 {%0,%1,%2,%3,%4,%5,%6,%7,%8,%9,%10,%11,%12,%13,%14,%15}, {%16,%17,%18,%19}, %20, 1, 1, 1, 0;"
    : "+f"(d[0]),"+f"(d[1]),"+f"(d[2]),"+f"(d[3]),"+f"(d[4]),"+f"(d[5]),"+f"(d[6]),"+f"(d[7]),"+f"(d[8]),"+f"(d[9]),"+f"(d[10]),"+f"(d[11]),"+f"(d[12]),"+f"(d[13]),"+f"(d[14]),"+f"(d[15])
    : "r"(a[0]),"r"(a[1]),"r"(a[2]),"r"(a[3]),"l"(db));
}
__device__ __forceinline__ void wg_g1r(float* d, const uint32_t* a, uint64_t db) {
  asm volatile("wgmma.mma_async.sync.aligned.m64n128k16.f32.bf16.bf16 {%0,%1,%2,%3,%4,%5,%6,%7,%8,%9,%10,%11,%12,%13,%14,%15,%16,%17,%18,%19,%20,%21,%22,%23,%24,%25,%26,%27,%28,%29,%30,%31,%32,%33,%34,%35,%36,%37,%38,%39,%40,%41,%42,%43,%44,%45,%46,%47,%48,%49,%50,%51,%52,%53,%54,%55,%56,%57,%58,%59,%60,%61,%62,%63}, {%64,%65,%66,%67}, %68, 1, 1, 1, 1;"
    : "+f"(d[0]),"+f"(d[1]),"+f"(d[2]),"+f"(d[3]),"+f"(d[4]),"+f"(d[5]),"+f"(d[6]),"+f"(d[7]),"+f"(d[8]),"+f"(d[9]),"+f"(d[10]),"+f"(d[11]),"+f"(d[12]),"+f"(d[13]),"+f"(d[14]),"+f"(d[15]),"+f"(d[16]),"+f"(d[17]),"+f"(d[18]),"+f"(d[19]),"+f"(d[20]),"+f"(d[21]),"+f"(d[22]),"+f"(d[23]),"+f"(d[24]),"+f"(d[25]),"+f"(d[26]),"+f"(d[27]),"+f"(d[28]),"+f"(d[29]),"+f"(d[30]),"+f"(d[31]),"+f"(d[32]),"+f"(d[33]),"+f"(d[34]),"+f"(d[35]),"+f"(d[36]),"+f"(d[37]),"+f"(d[38]),"+f"(d[39]),"+f"(d[40]),"+f"(d[41]),"+f"(d[42]),"+f"(d[43]),"+f"(d[44]),"+f"(d[45]),"+f"(d[46]),"+f"(d[47]),"+f"(d[48]),"+f"(d[49]),"+f"(d[50]),"+f"(d[51]),"+f"(d[52]),"+f"(d[53]),"+f"(d[54]),"+f"(d[55]),"+f"(d[56]),"+f"(d[57]),"+f"(d[58]),"+f"(d[59]),"+f"(d[60]),"+f"(d[61]),"+f"(d[62]),"+f"(d[63])
    : "r"(a[0]),"r"(a[1]),"r"(a[2]),"r"(a[3]),"l"(db));
}
__device__ __forceinline__ void wg_g1rb0(float* d, const uint32_t* a, uint64_t db) {
  asm volatile("wgmma.mma_async.sync.aligned.m64n96k16.f32.bf16.bf16 {%0,%1,%2,%3,%4,%5,%6,%7,%8,%9,%10,%11,%12,%13,%14,%15,%16,%17,%18,%19,%20,%21,%22,%23,%24,%25,%26,%27,%28,%29,%30,%31,%32,%33,%34,%35,%36,%37,%38,%39,%40,%41,%42,%43,%44,%45,%46,%47}, {%48,%49,%50,%51}, %52, 0, 1, 1, 1;"
    : "=f"(d[0]),"=f"(d[1]),"=f"(d[2]),"=f"(d[3]),"=f"(d[4]),"=f"(d[5]),"=f"(d[6]),"=f"(d[7]),"=f"(d[8]),"=f"(d[9]),"=f"(d[10]),"=f"(d[11]),"=f"(d[12]),"=f"(d[13]),"=f"(d[14]),"=f"(d[15]),"=f"(d[16]),"=f"(d[17]),"=f"(d[18]),"=f"(d[19]),"=f"(d[20]),"=f"(d[21]),"=f"(d[22]),"=f"(d[23]),"=f"(d[24]),"=f"(d[25]),"=f"(d[26]),"=f"(d[27]),"=f"(d[28]),"=f"(d[29]),"=f"(d[30]),"=f"(d[31]),"=f"(d[32]),"=f"(d[33]),"=f"(d[34]),"=f"(d[35]),"=f"(d[36]),"=f"(d[37]),"=f"(d[38]),"=f"(d[39]),"=f"(d[40]),"=f"(d[41]),"=f"(d[42]),"=f"(d[43]),"=f"(d[44]),"=f"(d[45]),"=f"(d[46]),"=f"(d[47])
    : "r"(a[0]),"r"(a[1]),"r"(a[2]),"r"(a[3]),"l"(db));
}
__device__ __forceinline__ void wg_g1a0(float* d, uint64_t da, uint64_t db) {
  asm volatile("wgmma.mma_async.sync.aligned.m64n128k16.f32.bf16.bf16 {%0,%1,%2,%3,%4,%5,%6,%7,%8,%9,%10,%11,%12,%13,%14,%15,%16,%17,%18,%19,%20,%21,%22,%23,%24,%25,%26,%27,%28,%29,%30,%31,%32,%33,%34,%35,%36,%37,%38,%39,%40,%41,%42,%43,%44,%45,%46,%47,%48,%49,%50,%51,%52,%53,%54,%55,%56,%57,%58,%59,%60,%61,%62,%63}, %64, %65, 0, 1, 1, 1, 1;"
    : "=f"(d[0]),"=f"(d[1]),"=f"(d[2]),"=f"(d[3]),"=f"(d[4]),"=f"(d[5]),"=f"(d[6]),"=f"(d[7]),"=f"(d[8]),"=f"(d[9]),"=f"(d[10]),"=f"(d[11]),"=f"(d[12]),"=f"(d[13]),"=f"(d[14]),"=f"(d[15]),"=f"(d[16]),"=f"(d[17]),"=f"(d[18]),"=f"(d[19]),"=f"(d[20]),"=f"(d[21]),"=f"(d[22]),"=f"(d[23]),"=f"(d[24]),"=f"(d[25]),"=f"(d[26]),"=f"(d[27]),"=f"(d[28]),"=f"(d[29]),"=f"(d[30]),"=f"(d[31]),"=f"(d[32]),"=f"(d[33]),"=f"(d[34]),"=f"(d[35]),"=f"(d[36]),"=f"(d[37]),"=f"(d[38]),"=f"(d[39]),"=f"(d[40]),"=f"(d[41]),"=f"(d[42]),"=f"(d[43]),"=f"(d[44]),"=f"(d[45]),"=f"(d[46]),"=f"(d[47]),"=f"(d[48]),"=f"(d[49]),"=f"(d[50]),"=f"(d[51]),"=f"(d[52]),"=f"(d[53]),"=f"(d[54]),"=f"(d[55]),"=f"(d[56]),"=f"(d[57]),"=f"(d[58]),"=f"(d[59]),"=f"(d[60]),"=f"(d[61]),"=f"(d[62]),"=f"(d[63])
    : "l"(da),"l"(db));
}
__device__ __forceinline__ void wg_g1a(float* d, uint64_t da, uint64_t db) {
  asm volatile("wgmma.mma_async.sync.aligned.m64n128k16.f32.bf16.bf16 {%0,%1,%2,%3,%4,%5,%6,%7,%8,%9,%10,%11,%12,%13,%14,%15,%16,%17,%18,%19,%20,%21,%22,%23,%24,%25,%26,%27,%28,%29,%30,%31,%32,%33,%34,%35,%36,%37,%38,%39,%40,%41,%42,%43,%44,%45,%46,%47,%48,%49,%50,%51,%52,%53,%54,%55,%56,%57,%58,%59,%60,%61,%62,%63}, %64, %65, 1, 1, 1, 1, 1;"
    : "+f"(d[0]),"+f"(d[1]),"+f"(d[2]),"+f"(d[3]),"+f"(d[4]),"+f"(d[5]),"+f"(d[6]),"+f"(d[7]),"+f"(d[8]),"+f"(d[9]),"+f"(d[10]),"+f"(d[11]),"+f"(d[12]),"+f"(d[13]),"+f"(d[14]),"+f"(d[15]),"+f"(d[16]),"+f"(d[17]),"+f"(d[18]),"+f"(d[19]),"+f"(d[20]),"+f"(d[21]),"+f"(d[22]),"+f"(d[23]),"+f"(d[24]),"+f"(d[25]),"+f"(d[26]),"+f"(d[27]),"+f"(d[28]),"+f"(d[29]),"+f"(d[30]),"+f"(d[31]),"+f"(d[32]),"+f"(d[33]),"+f"(d[34]),"+f"(d[35]),"+f"(d[36]),"+f"(d[37]),"+f"(d[38]),"+f"(d[39]),"+f"(d[40]),"+f"(d[41]),"+f"(d[42]),"+f"(d[43]),"+f"(d[44]),"+f"(d[45]),"+f"(d[46]),"+f"(d[47]),"+f"(d[48]),"+f"(d[49]),"+f"(d[50]),"+f"(d[51]),"+f"(d[52]),"+f"(d[53]),"+f"(d[54]),"+f"(d[55]),"+f"(d[56]),"+f"(d[57]),"+f"(d[58]),"+f"(d[59]),"+f"(d[60]),"+f"(d[61]),"+f"(d[62]),"+f"(d[63])
    : "l"(da),"l"(db));
}
__device__ __forceinline__ void wg_g1b(float* d, uint64_t da, uint64_t db) {
  asm volatile("wgmma.mma_async.sync.aligned.m64n96k16.f32.bf16.bf16 {%0,%1,%2,%3,%4,%5,%6,%7,%8,%9,%10,%11,%12,%13,%14,%15,%16,%17,%18,%19,%20,%21,%22,%23,%24,%25,%26,%27,%28,%29,%30,%31,%32,%33,%34,%35,%36,%37,%38,%39,%40,%41,%42,%43,%44,%45,%46,%47}, %48, %49, 1, 1, 1, 1, 1;"
    : "+f"(d[0]),"+f"(d[1]),"+f"(d[2]),"+f"(d[3]),"+f"(d[4]),"+f"(d[5]),"+f"(d[6]),"+f"(d[7]),"+f"(d[8]),"+f"(d[9]),"+f"(d[10]),"+f"(d[11]),"+f"(d[12]),"+f"(d[13]),"+f"(d[14]),"+f"(d[15]),"+f"(d[16]),"+f"(d[17]),"+f"(d[18]),"+f"(d[19]),"+f"(d[20]),"+f"(d[21]),"+f"(d[22]),"+f"(d[23]),"+f"(d[24]),"+f"(d[25]),"+f"(d[26]),"+f"(d[27]),"+f"(d[28]),"+f"(d[29]),"+f"(d[30]),"+f"(d[31]),"+f"(d[32]),"+f"(d[33]),"+f"(d[34]),"+f"(d[35]),"+f"(d[36]),"+f"(d[37]),"+f"(d[38]),"+f"(d[39]),"+f"(d[40]),"+f"(d[41]),"+f"(d[42]),"+f"(d[43]),"+f"(d[44]),"+f"(d[45]),"+f"(d[46]),"+f"(d[47])
    : "l"(da),"l"(db));
}
__device__ __forceinline__ void wg_g2h(float* d, uint64_t da, uint64_t db) {
  asm volatile("wgmma.mma_async.sync.aligned.m64n64k16.f32.bf16.bf16 {%0,%1,%2,%3,%4,%5,%6,%7,%8,%9,%10,%11,%12,%13,%14,%15,%16,%17,%18,%19,%20,%21,%22,%23,%24,%25,%26,%27,%28,%29,%30,%31}, %32, %33, 1, 1, 1, 0, 1;"
    : "+f"(d[0]),"+f"(d[1]),"+f"(d[2]),"+f"(d[3]),"+f"(d[4]),"+f"(d[5]),"+f"(d[6]),"+f"(d[7]),"+f"(d[8]),"+f"(d[9]),"+f"(d[10]),"+f"(d[11]),"+f"(d[12]),"+f"(d[13]),"+f"(d[14]),"+f"(d[15]),"+f"(d[16]),"+f"(d[17]),"+f"(d[18]),"+f"(d[19]),"+f"(d[20]),"+f"(d[21]),"+f"(d[22]),"+f"(d[23]),"+f"(d[24]),"+f"(d[25]),"+f"(d[26]),"+f"(d[27]),"+f"(d[28]),"+f"(d[29]),"+f"(d[30]),"+f"(d[31])
    : "l"(da),"l"(db));
}
__device__ __forceinline__ void wg_g2h0(float* d, uint64_t da, uint64_t db) {
  asm volatile("wgmma.mma_async.sync.aligned.m64n64k16.f32.bf16.bf16 {%0,%1,%2,%3,%4,%5,%6,%7,%8,%9,%10,%11,%12,%13,%14,%15,%16,%17,%18,%19,%20,%21,%22,%23,%24,%25,%26,%27,%28,%29,%30,%31}, %32, %33, 0, 1, 1, 0, 1;"
    : "=f"(d[0]),"=f"(d[1]),"=f"(d[2]),"=f"(d[3]),"=f"(d[4]),"=f"(d[5]),"=f"(d[6]),"=f"(d[7]),"=f"(d[8]),"=f"(d[9]),"=f"(d[10]),"=f"(d[11]),"=f"(d[12]),"=f"(d[13]),"=f"(d[14]),"=f"(d[15]),"=f"(d[16]),"=f"(d[17]),"=f"(d[18]),"=f"(d[19]),"=f"(d[20]),"=f"(d[21]),"=f"(d[22]),"=f"(d[23]),"=f"(d[24]),"=f"(d[25]),"=f"(d[26]),"=f"(d[27]),"=f"(d[28]),"=f"(d[29]),"=f"(d[30]),"=f"(d[31])
    : "l"(da),"l"(db));
}
__device__ __forceinline__ void wg_g20(float* d, uint64_t da, uint64_t db) {
  asm volatile("wgmma.mma_async.sync.aligned.m64n128k16.f32.bf16.bf16 {%0,%1,%2,%3,%4,%5,%6,%7,%8,%9,%10,%11,%12,%13,%14,%15,%16,%17,%18,%19,%20,%21,%22,%23,%24,%25,%26,%27,%28,%29,%30,%31,%32,%33,%34,%35,%36,%37,%38,%39,%40,%41,%42,%43,%44,%45,%46,%47,%48,%49,%50,%51,%52,%53,%54,%55,%56,%57,%58,%59,%60,%61,%62,%63}, %64, %65, 0, 1, 1, 0, 1;"
    : "=f"(d[0]),"=f"(d[1]),"=f"(d[2]),"=f"(d[3]),"=f"(d[4]),"=f"(d[5]),"=f"(d[6]),"=f"(d[7]),"=f"(d[8]),"=f"(d[9]),"=f"(d[10]),"=f"(d[11]),"=f"(d[12]),"=f"(d[13]),"=f"(d[14]),"=f"(d[15]),"=f"(d[16]),"=f"(d[17]),"=f"(d[18]),"=f"(d[19]),"=f"(d[20]),"=f"(d[21]),"=f"(d[22]),"=f"(d[23]),"=f"(d[24]),"=f"(d[25]),"=f"(d[26]),"=f"(d[27]),"=f"(d[28]),"=f"(d[29]),"=f"(d[30]),"=f"(d[31]),"=f"(d[32]),"=f"(d[33]),"=f"(d[34]),"=f"(d[35]),"=f"(d[36]),"=f"(d[37]),"=f"(d[38]),"=f"(d[39]),"=f"(d[40]),"=f"(d[41]),"=f"(d[42]),"=f"(d[43]),"=f"(d[44]),"=f"(d[45]),"=f"(d[46]),"=f"(d[47]),"=f"(d[48]),"=f"(d[49]),"=f"(d[50]),"=f"(d[51]),"=f"(d[52]),"=f"(d[53]),"=f"(d[54]),"=f"(d[55]),"=f"(d[56]),"=f"(d[57]),"=f"(d[58]),"=f"(d[59]),"=f"(d[60]),"=f"(d[61]),"=f"(d[62]),"=f"(d[63])
    : "l"(da),"l"(db));
}
__device__ __forceinline__ void wg_g2(float* d, uint64_t da, uint64_t db) {
  asm volatile("wgmma.mma_async.sync.aligned.m64n128k16.f32.bf16.bf16 {%0,%1,%2,%3,%4,%5,%6,%7,%8,%9,%10,%11,%12,%13,%14,%15,%16,%17,%18,%19,%20,%21,%22,%23,%24,%25,%26,%27,%28,%29,%30,%31,%32,%33,%34,%35,%36,%37,%38,%39,%40,%41,%42,%43,%44,%45,%46,%47,%48,%49,%50,%51,%52,%53,%54,%55,%56,%57,%58,%59,%60,%61,%62,%63}, %64, %65, 1, 1, 1, 0, 1;"
    : "+f"(d[0]),"+f"(d[1]),"+f"(d[2]),"+f"(d[3]),"+f"(d[4]),"+f"(d[5]),"+f"(d[6]),"+f"(d[7]),"+f"(d[8]),"+f"(d[9]),"+f"(d[10]),"+f"(d[11]),"+f"(d[12]),"+f"(d[13]),"+f"(d[14]),"+f"(d[15]),"+f"(d[16]),"+f"(d[17]),"+f"(d[18]),"+f"(d[19]),"+f"(d[20]),"+f"(d[21]),"+f"(d[22]),"+f"(d[23]),"+f"(d[24]),"+f"(d[25]),"+f"(d[26]),"+f"(d[27]),"+f"(d[28]),"+f"(d[29]),"+f"(d[30]),"+f"(d[31]),"+f"(d[32]),"+f"(d[33]),"+f"(d[34]),"+f"(d[35]),"+f"(d[36]),"+f"(d[37]),"+f"(d[38]),"+f"(d[39]),"+f"(d[40]),"+f"(d[41]),"+f"(d[42]),"+f"(d[43]),"+f"(d[44]),"+f"(d[45]),"+f"(d[46]),"+f"(d[47]),"+f"(d[48]),"+f"(d[49]),"+f"(d[50]),"+f"(d[51]),"+f"(d[52]),"+f"(d[53]),"+f"(d[54]),"+f"(d[55]),"+f"(d[56]),"+f"(d[57]),"+f"(d[58]),"+f"(d[59]),"+f"(d[60]),"+f"(d[61]),"+f"(d[62]),"+f"(d[63])
    : "l"(da),"l"(db));
}

template <int S, int PASS_AT = -1> __device__ __forceinline__ void conv_mma(float* acc, const uint32_t (*A)[4], uint64_t d0, int next_turn = 0) {
  wg_fence();
#pragma unroll
  for (int e = 0; e < 8; e++) {
    if (e == PASS_AT) nb_arrive(next_turn, 256);
#pragma unroll
    for (int i = 0; i < 4 - S; i++) {
      if (S == 0 && e == 0) wg_conv0(acc + 16 * i, A[e], d0 + (32 * i + 32) * 8);
      else wg_conv(acc + 16 * (i + S), A[e], d0 + (32 * i - 4 * e + 32) * 8);
    }
  }
  wg_commit();
}
__device__ __forceinline__ void conv_loadA(uint32_t (*A)[4], const uint32_t* ua, uint32_t x, uint32_t off) {
#pragma unroll
  for (int e = 0; e < 8; e++) {
    const uint32_t e0 = lds32(ua[0] + x + off + 512 * e), e1 = lds32(ua[1] + x + off + 512 * e), e2 = lds32(ua[2] + x + off + 512 * e);
    A[e][0] = prmt(e0, e1, 0x5432);
    A[e][1] = e1;
    A[e][2] = prmt(e1, e2, 0x5432);
    A[e][3] = e2;
  }
}
template <int J0, int J1> __device__ __forceinline__ void store_partials(const float* acc, uint32_t rb, uint32_t last) {
#pragma unroll
  for (int j = J0; j < J1; j += 2)
    stsm4t(j == 14 ? last : rb + j * 1024, pack2(acc[4 * j], acc[4 * j + 1]), pack2(acc[4 * j + 2], acc[4 * j + 3]),
           pack2(acc[4 * j + 4], acc[4 * j + 5]), pack2(acc[4 * j + 6], acc[4 * j + 7]));
}
__device__ __forceinline__ void filter_block(uint32_t src, uint32_t dst) {
  const uint4 a = lds128(src), c = lds128(src + 16);
  sts128(dst, prmt(c.w, 0, 0x1032), prmt(c.y, 0, 0x1032), prmt(a.w, 0, 0x1032), prmt(a.y, 0, 0x1032));
  sts128(dst ^ 16, prmt(c.z, 0, 0x1032), prmt(c.x, 0, 0x1032), prmt(a.z, 0, 0x1032), prmt(a.x, 0, 0x1032));
}

struct RowStat { float r0, h0, r1, h1; };

template <int J0, int J1, bool TAIL>
__device__ __forceinline__ void ffn_epi(const float* acc, const RowStat& rs, uint32_t* dst, uint32_t* dst2 = nullptr, int split = 0, int step = 0, bool six = false) {
#pragma unroll
  for (int j = J0; j < J1; j++) {
    float a[4];
#pragma unroll
    for (int e = 0; e < 4; e++) {
      const float gh = acc[4 * j + e] * ((e & 2) ? rs.h1 : rs.h0);
      const float u = acc[(TAIL ? 24 : 32) + 4 * j + e] * ((e & 2) ? rs.r1 : rs.r0);
      a[e] = fmaf(gh, tanh_fast(gh), gh) * u;
    }
    if (!TAIL) {
      dst[j * 32] = pack2(a[0], a[1]);
      dst[j * 32 + 256] = pack2(a[2], a[3]);
    } else if (j < 4 || six) {
      uint32_t* p = (j & ~1) < split ? dst : dst2;
      p[j * 32] = pack2(a[0], a[1]);
      p[j * 32 + step] = pack2(a[2], a[3]);
    }
  }
}

#define BAR(i) (bars + 8u * (uint32_t)(i))
constexpr uint32_t A_SLOTS = 0x5320321, A_AFTER = 0x5543210, G_SLOTS = 0x416540, G_AFTER = 0x432100;
#define QST_POS 3
#define KFY_POS 7
#define HELP_LAST 1
#define RPK_LD 7
#define AHEAD 3
#define HELPER_DELAY 5000

template <int KIND, int NKS, bool FIRST>
__device__ __forceinline__ void mma_unit(float* acc, uint64_t da, uint64_t db) {
  wg_fence();
#pragma unroll
  for (int ks = 0; ks < NKS; ks++) {
    const uint64_t a = da + (ks >> 2) * 1024 + (ks & 3) * (KIND == 2 ? 16 : 128), b = db + (KIND == 1 ? (ks >> 1) * 384 + (ks & 1) * 16 : (ks >> 2) * 1024 + (ks & 3) * 128);
    if (FIRST && ks == 0) { if (KIND == 0) wg_g1a0(acc, a, b); else wg_g20(acc, a, b); }
    else { if (KIND == 0) wg_g1a(acc, a, b); else if (KIND == 1) wg_g1b(acc, a, b); else wg_g2(acc, a, b); }
  }
  wg_commit();
}
template <int NKS, bool FIRST> __device__ __forceinline__ void half_unit(float* acc, uint64_t da, uint64_t db) {
  wg_fence();
  if (FIRST) wg_g2h0(acc, da, db); else wg_g2h(acc, da, db);
#pragma unroll
  for (int ks = 1; ks < NKS; ks++) wg_g2h(acc, da + (ks >> 2) * 1024 + (ks & 3) * 16, db + ks * 128);
  wg_commit();
}
__device__ __forceinline__ void row_stats(uint32_t a, float* hs, float* hq) {
  uint32_t f[2][4];
  ldsm4t(f[0], a); ldsm4t(f[1], a + 2048);
#pragma unroll
  for (int i = 0; i < 8; i++) {
    const float lo = blo(f[i >> 2][i & 3]), hi = bhi(f[i >> 2][i & 3]);
    hs[i & 3] += lo + hi; hq[i & 3] = fmaf(lo, lo, fmaf(hi, hi, hq[i & 3]));
  }
}

__device__ __forceinline__ int pair_role(uint32_t block) {
  const int tp = (int)(block >> 1) - 4;
  const int a = (tp & 7) * 8 + (tp >> 3);
  const int q = ((tp - 32) * 37) >> 8, c = (1 + tp - 32 - 7 * q) * 8 + 4 + q;
  return tp < 0 ? 8 + tp : tp < 32 ? a : c;
}

__global__ void __cluster_dims__(2, 1, 1) __launch_bounds__(384, 1) fused_kernel(const __grid_constant__ Params P) {
  extern __shared__ __align__(1024) unsigned char smem_raw[];
  const uint32_t sb = smem_u32(smem_raw);
  const int tid = threadIdx.x, lane = tid & 31;
  const int warp = __shfl_sync(0xffffffffu, tid >> 5, 0);
  const uint32_t bars = sb + BARS;

  if (HELP_LAST ? blockIdx.x >= NMAIN : blockIdx.x < NHELP) {
    const CUtensorMap* tm = (blockIdx.x & 2) ? &P.tmWu : &P.tmWg;
    const uint32_t hb = BAR(2 * warp), buf = sb + warp * 16384;
    const int col = 64 * (2 * warp + (blockIdx.x & 1));
    if (warp < 11) {
      if (elect_one()) {
        mbar_init(hb, 1); mbar_init(hb + 8, 1);
        fence_async_smem();
        const long long t0 = clock64();
        while (clock64() - t0 < HELPER_DELAY) { }
        mbar_expect(hb, 8192);
        tma3d(buf, tm, hb, col, 0, 0);
        mbar_expect(hb + 8, 8192);
        tma3d(buf + 8192, tm, hb + 8, col, 0, 64);
      }
      __syncwarp();
      const uint32_t a0 = buf + (lane >> 3) * 128 + (((lane & 7) ^ (lane >> 3)) << 4), a1 = buf + ((lane >> 3) + 4) * 128 + (((lane & 7) ^ ((lane >> 3) + 4)) << 4);
      float s[8];
#pragma unroll
      for (int i = 0; i < 8; i++) s[i] = 0.f;
#pragma unroll 1
      for (int u = 0; u < 8; u++) {
        const uint32_t hf = u & 1;
        mbar_wait_aux(hb + 8 * hf, (u >> 1) & 1);
        uint4 v[8], w[8];
#pragma unroll
        for (int i = 0; i < 8; i++) { v[i] = lds128(a0 + hf * 8192 + i * 1024); w[i] = lds128(a1 + hf * 8192 + i * 1024); }
#pragma unroll
        for (int i = 0; i < 8; i++) s[0] -= blo(v[i].x) + blo(w[i].x);
        if (__all_sync(0xffffffffu, __float_as_uint(s[0]) != 0xffffffffu || P.zero == 0) && u < 6 && elect_one()) {
          mbar_expect(hb + 8 * hf, 8192);
          tma3d(buf + hf * 8192, tm, hb + 8 * hf, col, (u >> 1) + 1, 64 * hf);
        }
#pragma unroll
        for (int i = 0; i < 8; i++) {
          s[1] -= bhi(v[i].x) + bhi(w[i].x); s[2] -= blo(v[i].y) + blo(w[i].y); s[3] -= bhi(v[i].y) + bhi(w[i].y);
          s[4] -= blo(v[i].z) + blo(w[i].z); s[5] -= bhi(v[i].z) + bhi(w[i].z); s[6] -= blo(v[i].w) + blo(w[i].w); s[7] -= bhi(v[i].w) + bhi(w[i].w);
        }
      }
#pragma unroll
      for (int i = 0; i < 8; i++) { s[i] += __shfl_xor_sync(0xffffffffu, s[i], 8); s[i] += __shfl_xor_sync(0xffffffffu, s[i], 16); }
      uint32_t hi[4], lo[4];
#pragma unroll
      for (int i = 0; i < 4; i++) { hi[i] = pack2(s[2 * i], s[2 * i + 1]); lo[i] = pack2(s[2 * i] - blo(hi[i]), s[2 * i + 1] - bhi(hi[i])); }
      if (lane < 16) {
        uint4* o = reinterpret_cast<uint4*>(P.colsum + ((blockIdx.x & 2) + (lane >> 3)) * 704 + col / 2) + (lane & 7);
        *o = lane < 8 ? make_uint4(hi[0], hi[1], hi[2], hi[3]) : make_uint4(lo[0], lo[1], lo[2], lo[3]);
      }
    }
    __syncthreads();
    if (tid == 0) red_release(&P.cnt[C_CS * CNT_STRIDE]);
    TLREC(0);
    return;
  }

  const int rank = blockIdx.x & 1;
  const int pair = pair_role(blockIdx.x);
  const int mb = 2 * pair + rank;
#define FFN_ROLE() int cs_, tp; { uint32_t b_; asm volatile("mov.u32 %0, %%ctaid.x;" : "=r"(b_)); const int p_ = pair_role(b_); \
    cs_ = ((p_ >> 3) & 1) * 4 + (p_ & 3); tp = (p_ >> 4) * 2 + ((p_ >> 2) & 1); }

#define LOAD_KV(j) do { const int row_ = 128 * (2 * (j) + rank); mbar_expect(BAR(B_RAWF) + 8 * (j), RAWK_BLK + 2048); \
    tma2d(sb + RAWK + (j) * RAWK_BLK, &P.tmK, BAR(B_RAWF) + 8 * (j), 8 * pair, row_ - 8); \
    tma2d(sb + RAWV + (j) * 2048, &P.tmV, BAR(B_RAWF) + 8 * (j), 8 * pair, row_); } while (0)
#define LOAD_RPK() do { mbar_expect(BAR(B_RPK), 6144); _Pragma("unroll") for (int w_ = 0; w_ < 2; w_++) \
    asm volatile("cp.async.bulk.tensor.4d.shared::cluster.global.mbarrier::complete_tx::bytes [%0], [%1, {%3,%4,%5,%6}], [%2];" ::"r"(sb + RPK + w_ * 3072), \
                 "l"(w_ ? &P.tmU3 : &P.tmG3), "r"(BAR(B_RPK)), "r"(0), "r"(32 * (mb & 3)), "r"(128 + (mb < 112 ? 6 * (mb >> 4) : 40)), "r"((mb >> 2) & 3) : "memory"); } while (0)
#define LOAD_Q(j) do { mbar_expect(BAR(B_RAWQF) + 8 * (j), 4096); \
    tma2d(sb + RAWQ + (j) * 4096, &P.tmQ, BAR(B_RAWQF) + 8 * (j), 8 * pair, 128 * (4 * (j) + rank)); \
    tma2d(sb + RAWQ + (j) * 4096 + 2048, &P.tmQ, BAR(B_RAWQF) + 8 * (j), 8 * pair, 128 * (4 * (j) + 2 + rank)); } while (0)

#define FRESH_IDS() uint32_t tid_, blk_; \
    asm volatile("mov.u32 %0, %%tid.x;\nmov.u32 %1, %%ctaid.x;" : "=r"(tid_), "=r"(blk_)); \
    const int tid = tid_, lane = tid & 31, warp = __shfl_sync(0xffffffffu, tid >> 5, 0), rank = blk_ & 1, pair = pair_role(blk_), mb = 2 * pair + rank; \
    mbar_wait(BAR(B_SMALL), 0); \
    const unsigned done = lds32(sb + SMALL)

  if (warp == 8) {
    if (elect_one()) {
#pragma unroll
      for (int i = 0; i < 16; i++) mbar_init(BAR(i), 1);
      mbar_init(BAR(B_SMALL), 1); mbar_init(BAR(B_RPK), 1);
      fence_async_smem();
      mbar_expect(BAR(B_SMALL), 96);
      bulk_ld(sb + SMALL, &P.cnt[C_DONE * CNT_STRIDE], 16, BAR(B_SMALL));
      bulk_ld(sb + SMALL + 16, P.ssmD + 8 * pair, 16, BAR(B_SMALL));
      bulk_ld(sb + SMALL + 32, P.shiftk + 32 * pair, 64, BAR(B_SMALL));
      mbar_expect(BAR(B_QSLAB), 16384);
      bulk_ld(sb + QSLAB, P.q + (size_t)mb * 16 * DM, 16384, BAR(B_QSLAB));
    }
    __syncwarp();
    nb_arrive(NB_INIT, 384);
    asm volatile("barrier.cluster.arrive.relaxed.aligned;" ::: "memory");
  } else {
    if (warp == 9) {
      if (elect_one()) {
#pragma unroll
        for (int i = 0; i < 5; i++) mbar_init(BAR(B_UF + i), 1);
        mbar_init(BAR(B_RAWDONE), 20); mbar_init(BAR(B_CONVDONE), 16); mbar_init(BAR(B_CS), 1); mbar_init(BAR(B_KT2), 2); mbar_init(BAR(B_PUB), 2); mbar_init(BAR(B_PFREE), 4); mbar_init(BAR(B_PFREE + 1), 4); mbar_init(BAR(B_EXCH), 1); mbar_init(BAR(B_EXCH + 1), 1);
#pragma unroll
        for (int i = 0; i < 4; i++) mbar_expect(BAR(B_UF + i), 4096);
        mbar_expect(BAR(B_XQF), 16384);
        mbar_expect(BAR(B_EXCH), 8192); mbar_expect(BAR(B_EXCH + 1), 8192);
        asm volatile("fence.mbarrier_init.release.cluster;" ::: "memory");
      }
    } else if (warp == 10) {
      if (elect_one()) {
#pragma unroll
        for (int i = 0; i < 3; i++) { mbar_init(BAR(B_WF + i), 1); mbar_init(BAR(B_WE + i), 16); }
#pragma unroll
        for (int i = 0; i < 7; i++) mbar_init(BAR(B_XF + i), 1);
#pragma unroll
        for (int i = 0; i < 19; i++) mbar_init(BAR(B_AF + i), i < 13 ? 1 : 8);
#pragma unroll
        for (int i = 0; i < 5; i++) mbar_init(BAR(B_SIG + i), i == 1 ? 9 : 8);
        asm volatile("fence.mbarrier_init.release.cluster;" ::: "memory");
        fence_async_smem();
      }
    } else if (warp == 11) {
      if (lane < 10) asm volatile("prefetch.tensormap [%0];" ::"l"(&P.tmK + lane) : "memory");
      if (lane < 16) sts128(sb + UPAD + lane * 16, 0, 0, 0, 0);
      if (lane < 24) { sts128(sb + RED + lane * 16, 0, 0, 0, 0); sts128(sb + RED + RED_WG + lane * 16, 0, 0, 0, 0); }
    } else {
      sts128(sb + KPAD + tid * 16, 0, 0, 0, 0);
    }
    __syncwarp();
    nb_sync(NB_INIT, 384);
    asm volatile("barrier.cluster.arrive.relaxed.aligned;" ::: "memory");
  }

  if (warp < 8) {
    asm volatile("setmaxnreg.inc.sync.aligned.u32 224;");
    FRESH_IDS();
    uint2 small;
    lds64(small.x, small.y, sb + SMALL + 16 + rank * 8);
    const uint32_t dk = prmt(small.x, small.y, (warp & 4) ? 0x7632 : 0x5410);
    const uint32_t tagw = (~done << 24) & 0x80000000u;
    const int wg = warp >> 2, wq = warp & 3, g = lane >> 2, t = lane & 3;
    const int wtid = tid & 127;
    const uint32_t barsx = mapa(bars, lane & 1);
#define TURN_WAIT() nb_sync(NB_TURN + wg, 256)
#define TURN_PASS() nb_arrive(NB_TURN + (wg ^ 1), 256)
    if (wg == 1) TURN_PASS();
    {
      {
        mbar_wait(BAR(B_QSLAB), 0);
        TLW(56);
        const int r = 2 * warp + (lane >> 4);
        uint4 v[4];
#pragma unroll
        for (int i = 0; i < 4; i++) v[i] = lds128(sb + QSLAB + r * 1024 + (lane & 15) * 16 + i * 256);
        const float piv = blo(__shfl_sync(0xffffffffu, v[0].x, lane & 16));
        float s[4] = {0.f, 0.f, 0.f, 0.f}, q2[4] = {0.f, 0.f, 0.f, 0.f};
#pragma unroll
        for (int i = 0; i < 4; i++) {
          const uint32_t w[4] = {v[i].x, v[i].y, v[i].z, v[i].w};
#pragma unroll
          for (int e = 0; e < 4; e++) {
            const float lo = blo(w[e]) - piv, hi = bhi(w[e]) - piv;
            s[e] += lo + hi; q2[e] = fmaf(lo, lo, fmaf(hi, hi, q2[e]));
          }
        }
        float ss = (s[0] + s[1]) + (s[2] + s[3]), qq = (q2[0] + q2[1]) + (q2[2] + q2[3]);
#pragma unroll
        for (int o = 1; o < 16; o <<= 1) { ss += __shfl_xor_sync(0xffffffffu, ss, o); qq += __shfl_xor_sync(0xffffffffu, qq, o); }
        const float md = ss * (1.f / DM);
        const float var = fmaxf(fmaf(-md, md, qq * (1.f / DM)), 0.f);
        uint32_t vv = pack2(var, var);
        vv = pack2(blo(vv) + 1e-5f, 0.f);
        vv = pack2(sqrt_fast(blo(vv)), 0.f);
        const uint32_t rw = (__float_as_uint(rcp_fast(blo(vv))) & 0x7fffffffu) | tagw;
        const float mean = md + piv, mean2 = __shfl_xor_sync(0xffffffffu, mean, 16);
        const uint32_t rw2 = __shfl_xor_sync(0xffffffffu, rw, 16);
        if (lane == 0) asm volatile("st.relaxed.gpu.global.v4.u32 [%0], {%1,%2,%3,%4};" ::"l"(P.qstat + warp * 128 + mb), "r"(pack2(mean, mean2)), "r"(rw), "r"(rw2), "r"(0) : "memory");
        TLW(20);
        asm volatile("barrier.cluster.wait.aligned;" ::: "memory");
      }

      const uint32_t red = sb + RED + wg * RED_WG;
      uint32_t ua[3];
#pragma unroll
      for (int i = 0; i < 3; i++) {
        const int W = 8 * wq + g + 2 * t - 8 + i;
        ua[i] = sb + UT + (W >> 4) * 256 + (((wg ^ (W >> 4)) & 1) << 6) + (W & 3) * 16 + ((W >> 2) & 3) * 4;
      }
      const uint32_t rowo = wtid * 128, sx = (wtid & 7) << 4;
      const int pa = 8 * (lane >> 4) + (lane & 7) + wq;
      const uint32_t rb = red + pa * 128 + (((2 * wq + ((lane >> 3) & 1)) ^ (pa & 7)) << 4);
      const uint32_t rlast = pa >= 16 ? sb + DUMMY : rb + 14 * 1024;
      uint32_t A0[8][4], A1[8][4], B0[8][4];
      float ri[16];
      uint32_t m2[8] = {0, 0, 0, 0, 0, 0, 0, 0};
      float aX[64];
      float* aY = aX;
      uint32_t u[8], x[8], q[8];
#define UX_ADDR() int wt = wtid; asm volatile("" : "+r"(wt));   \
        const uint32_t go = (wt >> 1) * 256 + it * 128 + (wt & 1) * 8, xo = sb + XT + go + (((wg << 2) ^ ((wt >> 1) & 7)) << 4)
      auto prepare = [&](int it) {
        UX_ADDR();
        const uint32_t uo = sb + UT + go + (((wg ^ (wt >> 1)) & 1) << 6);
#pragma unroll
        for (int i = 0; i < 4; i++) lds64(u[i], u[4 + i], uo + 16 * i);
        if (it == 1) {
#pragma unroll
          for (int i = 0; i < 4; i++) lds64(x[i], x[4 + i], xo ^ (16 * i));
#pragma unroll
          for (int i = 0; i < 8; i++) {
            const uint32_t d = bsub2(x[i], m2[i]);
            q[i] = pack2(blo(d) * fabsf(ri[2 * i]), bhi(d) * fabsf(ri[2 * i + 1]));
            asm volatile("" : "+r"(q[i]));
          }
        }
      };
      auto finish = [&](int it) {
        const int cl = wg + 2 * it;
        UX_ADDR();
        const uint32_t rowo = wt * 128, sx = (wt & 7) << 4;
        wg_wait<0>();
        reg_fence<16>(aX + 48);
        TLW(8 + 2 * cl);
        store_partials<12, 16>(aX, rb, rlast);
        nb_sync(NB_WG + wg, 128);
        uint4 p[8];
#pragma unroll
        for (int i = 0; i < 8; i++) p[i] = lds128(red + rowo + ((i << 4) ^ sx));
        const uint32_t D2 = prmt(dk, dk, it ? 0x3232 : 0x1010);
#define SUMP(C, H) badd2(badd2(p[H].C, p[2 + H].C), badd2(p[4 + H].C, p[6 + H].C))
        const uint32_t ev[4] = {SUMP(x, 0), SUMP(y, 0), SUMP(z, 0), SUMP(w, 0)}, od[4] = {SUMP(x, 1), SUMP(y, 1), SUMP(z, 1), SUMP(w, 1)};
#undef SUMP
#pragma unroll
        for (int i = 0; i < 8; i++) u[i] = bfma2(u[i], D2, prmt(ev[i >> 1], od[i >> 1], (i & 1) ? 0x7632 : 0x5410));
        if (it == 0) {
#pragma unroll
          for (int i = 0; i < 8; i++) {
            u[i] = pack2(blo(u[i]) * fabsf(ri[2 * i]), bhi(u[i]) * fabsf(ri[2 * i + 1]));
            asm volatile("" : "+r"(u[i]));
          }
          TLW(55);
          mbar_wait_cl(BAR(B_XQF), 0);
          TLW(57);
#pragma unroll
          for (int i = 0; i < 4; i++) lds64(x[i], x[4 + i], xo ^ (16 * i));
#pragma unroll
          for (int i = 0; i < 8; i++) q[i] = bsub2(x[i], m2[i]);
        }
#pragma unroll
        for (int i = 0; i < 8; i++) x[i] = bfma2(q[i], u[i], x[i]);
        uint4* hp = reinterpret_cast<uint4*>(P.hT + (size_t)(cl * 128 + mb) * S_LEN + 128 * (wt >> 3)) + (wt & 7);
        hp[0] = make_uint4(x[0], x[1], x[2], x[3]);
        hp[8] = make_uint4(x[4], x[5], x[6], x[7]);
        __syncwarp();
        if (lane == 0) mbar_arrive(BAR(B_SIG) + 8 * it);
        if (lane < 2) mbar_arrive_cl(barsx + 8 * (B_RAWDONE + it));
        TLW(9 + 2 * cl);
      };
      const uint32_t dX = mkdesc(sb + KPAD + wg * 32, 16), dY = dX + 4;
      uint64_t ud;
      mbar_wait(BAR(B_KFF), 0);
      filter_block(sb + KRAW + wg * 4096 + wtid * 32, sb + KT + rowo + (((wg * 2) << 4) ^ sx));
      fence_async_smem();
      mbar_wait_cl(BAR(B_UF), 0);
      TLW(3 + wg);
      conv_loadA(A0, ua, 0, 0);
      ud = udesc(dX, P.hi_sw);
      TURN_WAIT();
      conv_mma<0, 6>(aX, A0, ud, NB_TURN + (wg ^ 1));
      conv_loadA(B0, ua, 128, 0);
      mbar_wait_cl(BAR(B_UF + 1), 0);
      conv_loadA(A1, ua, 0, 4096);
      ud = udesc(dX, P.hi_sw);
      TURN_WAIT();
      conv_mma<1, 5>(aX, A1, ud, NB_TURN + (wg ^ 1));
      wg_wait<1>();
      reg_fence<16>(aX);
      store_partials<0, 4>(aX, rb, rlast);
      mbar_wait_cl(BAR(B_UF + 2), 0);
      conv_loadA(A0, ua, 0, 8192);
      ud = udesc(dX, P.hi_sw);
      conv_mma<2>(aX, A0, ud);
      TLW(5 + wg);
      mbar_wait(BAR(B_QST), 0);
      {
        uint4 st[8];
#pragma unroll
        for (int i = 0; i < 8; i++) st[i] = lds128(sb + QST + i * 2048 + wtid * 16);
#pragma unroll 1
        for (int spin = 0; spin < SPIN_LIMIT; spin++) {
          uint32_t bad = 0;
#pragma unroll
          for (int i = 0; i < 8; i++) bad |= (st[i].y ^ tagw) | (st[i].z ^ tagw);
          if (!__any_sync(0xffffffffu, (int)bad < 0)) break;
#pragma unroll
          for (int i = 0; i < 8; i++) st[i] = ldg_relaxed4(P.qstat + i * 128 + wtid);
        }
#pragma unroll
        for (int i = 0; i < 8; i++) { m2[i] = st[i].x; ri[2 * i] = __uint_as_float(st[i].y); ri[2 * i + 1] = __uint_as_float(st[i].z); }
        TLW(53 + wg);
      }
      wg_wait<1>();
      ud = udesc(dX, P.hi_sw);
      TLW(26 + wg);
      mbar_wait_cl(BAR(B_UF + 3), 0);
      TLW(16 + wg);
      conv_loadA(A1, ua, 0, 12288);
      conv_mma<3>(aX, A1, ud);
      prepare(0);
      wg_wait<1>();
      reg_fence<32>(aX + 16);
      store_partials<4, 12>(aX, rb, rlast);
      finish(0);
      mbar_wait(BAR(B_KT2), 0);
      ud = udesc(dY, P.hi_sw);
      TURN_WAIT();
      conv_mma<0, 6>(aY, B0, ud, NB_TURN + (wg ^ 1));
      conv_loadA(A0, ua, 128, 4096);
      conv_loadA(A1, ua, 128, 8192);
      ud = udesc(dY, P.hi_sw);
      TURN_WAIT();
      conv_mma<1, 5>(aY, A0, ud, NB_TURN + (wg ^ 1));
      wg_wait<1>();
      conv_loadA(B0, ua, 128, 12288);
      reg_fence<16>(aY);
      store_partials<0, 4>(aY, rb, rlast);
      ud = udesc(dY, P.hi_sw);
      TURN_WAIT();
      conv_mma<2>(aY, A1, ud);
      conv_mma<3, 0>(aY, B0, ud, NB_TURN + (wg ^ 1));
      prepare(1);
      wg_wait<2>();
      reg_fence<16>(aY + 16);
      store_partials<4, 8>(aY, rb, rlast);
      wg_wait<1>();
      reg_fence<16>(aY + 32);
      store_partials<8, 12>(aY, rb, rlast);
      finish(1);
    }

    FFN_ROLE();
    float accA[64], accB[64], accC[48];
    const uint32_t dAx = mkdesc(sb + wg * 8192, 16), dAa = mkdesc(sb + wg * 8192, 128), dB = mkdesc(sb, 8192), dB3 = mkdesc(sb, 128);
    const uint64_t dCs = mkdesc(sb + CSM, 1024) | (0x40000000ull << 32);
    uint32_t* actp = reinterpret_cast<uint32_t*>(P.act) + (size_t)(2 * tp + rank) * 22 * 4096 + (8 * wg + 2 * wq) * 256 + lane;
    RowStat rs;
    uint32_t m0, m1;
    const int tw_ = NB_GATE + wg, tp_ = NB_GATE + (wg ^ 1), tn_ = wg ? 256 : 288;
    if (wg == 0) TURN_WAIT(); else nb_arrive(NB_GATE, 288);
#define SCHED_FENCE() asm volatile("{\n.reg .pred p;\n.reg .u32 t;\nLF_%=:\nmov.u32 t, %%clock;\nsetp.lt.u32 p, t, %0;\n@p bra LF_%=;\n}" ::"r"(P.zero) : "memory")
#define DONE(U) do { wg_wait<0>(); if ((U) < 9) { if (lane < 2) mbar_arrive_cl(barsx + 8 * (B_WE + (U) % 3)); } else if (lane == 0) mbar_arrive(BAR(B_UD - 9) + 8 * (U)); } while (0)
#define ISSUE(U, ALO, AHI, BLO, BHI, CALL) do { const uint64_t ua_ = udesc(ALO, AHI), ub_ = udesc(BLO, BHI); SCHED_FENCE(); nb_sync(tw_, tn_); TL2(8 + (U)); CALL; nb_arrive(tp_, 544 - tn_); } while (0)
#define G1(U, XS, ACC, FIRST, PRE) ISSUE(U, dAx + (XS) * 2048, P.hi_sw, dB + (4 + (U) % 3) * 2048, P.hi_sw, PRE; (mma_unit<0, 8, FIRST>(ACC, ua_, ub_)))
#define G1B(U, XS, FIRST, PRE) ISSUE(U, dAx + (XS) * 2048, P.hi_sw, dB3 + (4 + (U) % 3) * 2048, P.hi_w3, PRE; (mma_unit<1, 8, FIRST>(accC, ua_, ub_)))
#define MEANS(p) const uint32_t mm##p[4] = {t == p ? m0 : 0u, t == p ? m1 : 0u, 0u, 0u}
#define ACT_DONE(p) do { __syncwarp(); if (lane == 0) mbar_arrive(BAR(B_SIG + 2 + (p))); } while (0)
    {
      const uint32_t hsa = sb + XR + (cs_ >> 1) * 16384 + (cs_ & 1) * 4096 + wg * 8192 + ((lane & 7) + 8 * (lane >> 4)) * 128 + (((2 * wq + ((lane >> 3) & 1)) ^ (lane & 7)) << 4);
      uint4* hp = P.hstat + (size_t)(2 * tp + rank) * 512 + 8 * warp + g;
      float hs[4] = {0.f, 0.f, 0.f, 0.f}, hq[4] = {0.f, 0.f, 0.f, 0.f};
      if (wg == 1) mbar_wait(BAR(B_X0B), 0);
      G1(0, 0, accA, true, );
      DONE(0);
      G1(1, 1, accA, false, );
      SCHED_FENCE();
      row_stats(hsa, hs, hq);
      reg_fence<4>(hs); reg_fence<4>(hq);
      SCHED_FENCE();
      DONE(1);
      G1(2, 0, accB, true, );
      DONE(2);
      G1(3, 1, accB, false, );
      mbar_wait(BAR(B_XF + 2) + 8 * (cs_ >> 2), 0);
      row_stats(hsa + 65536, hs, hq);
      reg_fence<4>(hs); reg_fence<4>(hq);
      SCHED_FENCE();
      DONE(3);
      float s0 = hs[0] + hs[2], q0 = hq[0] + hq[2], s1 = hs[1] + hs[3], q1 = hq[1] + hq[3];
#pragma unroll
      for (int o = 1; o < 4; o <<= 1) {
        s0 += __shfl_xor_sync(0xffffffffu, s0, o); s1 += __shfl_xor_sync(0xffffffffu, s1, o);
        q0 += __shfl_xor_sync(0xffffffffu, q0, o); q1 += __shfl_xor_sync(0xffffffffu, q1, o);
      }
      if (t == 0) asm volatile("st.relaxed.gpu.global.v4.u32 [%0], {%1,%2,%3,%4};" ::"l"(hp + cs_ * 64), "r"(__float_as_uint(s0)), "r"((__float_as_uint(q0) & 0x7fffffffu) | tagw),
                               "r"(__float_as_uint(s1)), "r"((__float_as_uint(q1) & 0x7fffffffu) | tagw) : "memory");
      G1(4, 2, accA, false, );
      DONE(4);
      uint4 v0 = ldg_relaxed4(hp + t * 128), v1 = ldg_relaxed4(hp + t * 128 + 64);
      G1(5, 3, accA, false, );
#pragma unroll 1
      for (int spin = 0; spin < SPIN_LIMIT; spin++) {
        if (!__any_sync(0xffffffffu, (int)((v0.y ^ tagw) | (v0.w ^ tagw) | (v1.y ^ tagw) | (v1.w ^ tagw)) < 0)) break;
        v0 = ldg_relaxed4(hp + t * 128); v1 = ldg_relaxed4(hp + t * 128 + 64);
      }
      TLW(44 + wg);
      s0 = __uint_as_float(v0.x) + __uint_as_float(v1.x); q0 = fabsf(__uint_as_float(v0.y)) + fabsf(__uint_as_float(v1.y));
      s1 = __uint_as_float(v0.z) + __uint_as_float(v1.z); q1 = fabsf(__uint_as_float(v0.w)) + fabsf(__uint_as_float(v1.w));
#pragma unroll
      for (int o = 1; o < 4; o <<= 1) {
        s0 += __shfl_xor_sync(0xffffffffu, s0, o); s1 += __shfl_xor_sync(0xffffffffu, s1, o);
        q0 += __shfl_xor_sync(0xffffffffu, q0, o); q1 += __shfl_xor_sync(0xffffffffu, q1, o);
      }
      s0 *= (1.f / DM); s1 *= (1.f / DM);
      m0 = pack2(s0, s0); m1 = pack2(s1, s1);
      MEANS(0);
      SCHED_FENCE();
      DONE(5);
      TLW(18 + wg);
      G1(6, 2, accB, false, wg_fence(); wg_g1r(accA, mm0, dCs); wg_commit());
      SCHED_FENCE();
      uint32_t v = pack2(fmaxf(fmaf(-s0, s0, q0 * (1.f / DM)), 0.f), fmaxf(fmaf(-s1, s1, q1 * (1.f / DM)), 0.f));
      v = pack2(blo(v) + 1e-5f, bhi(v) + 1e-5f);
      v = pack2(sqrt_fast(blo(v)), sqrt_fast(bhi(v)));
      rs.r0 = rcp_fast(blo(v)); rs.r1 = rcp_fast(bhi(v));
      rs.h0 = 0.5f * rs.r0; rs.h1 = 0.5f * rs.r1;
      wg_wait<1>();
    }
    reg_fence<64>(accA);
    ffn_epi<0, 3, false>(accA, rs, actp + cs_ * 4096);
    SCHED_FENCE();
    DONE(6);
    ffn_epi<3, 5, false>(accA, rs, actp + cs_ * 4096);
    MEANS(1);
    G1(7, 3, accB, false, wg_fence(); wg_g1r(accB, mm1, dCs));
    SCHED_FENCE();
    ffn_epi<5, 8, false>(accA, rs, actp + cs_ * 4096);
    ACT_DONE(0);
    SCHED_FENCE();
    DONE(7);
    reg_fence<64>(accB);
    TLW(22 + wg);
    ffn_epi<0, 2, false>(accB, rs, actp + (8 + cs_) * 4096);
    MEANS(2);
    G1B(8, 0, false, wg_fence(); wg_g1rb0(accC, mm2, dCs));
    SCHED_FENCE();
    ffn_epi<2, 6, false>(accB, rs, actp + (8 + cs_) * 4096);
    SCHED_FENCE();
    DONE(8);
    ffn_epi<6, 8, false>(accB, rs, actp + (8 + cs_) * 4096);
    ACT_DONE(1);
    const int off3 = cs_ < 7 ? 6 * cs_ : 40;
    int split3 = 8 - (off3 & 7);
    uint32_t* act3 = actp + (16 + (off3 >> 3)) * 4096 + (off3 & 7) * 32 - (cs_ < 7 ? 0 : warp * 256);
    asm volatile("" : "+l"(act3), "+r"(split3));
#pragma unroll 1
    for (int u = 9; u < 12; u++) {
      ISSUE(u, dAx + (u - 8) * 2048, P.hi_sw, dB3 + (u - 5) * 2048, P.hi_w3, (mma_unit<1, 8, false>(accC, ua_, ub_)));
      DONE(u);
    }
    reg_fence<48>(accC);
    TLW(24 + wg);
    ffn_epi<0, 6, true>(accC, rs, act3, act3 + 4096 - 256, split3, cs_ < 7 ? 256 : 128, cs_ < 6);
    ACT_DONE(2);
    ISSUE(12, dAa + 2048, P.hi_no, dB, P.hi_sw, (mma_unit<2, 8, true>(accB, ua_, ub_)));
#pragma unroll 1
    for (int u = 13; u < 16; u++) {
      DONE(u - 1);
      ISSUE(u, dAa + ((A_SLOTS >> (4 * u - 48)) & 7) * 2048, P.hi_no, dB + ((G_SLOTS >> (4 * u - 48)) & 7) * 2048, P.hi_sw, (mma_unit<2, 8, false>(accB, ua_, ub_)));
    }
    const uint32_t ex = sb + wg * 8192 + wtid * 16;
    const uint32_t rex = mapa(ex, rank ^ 1), rbar = mapa(BAR(B_EXCH + wg), rank ^ 1);
    const uint32_t stg = sb + 16384 + warp * 2048;
    const uint32_t rowa = stg + (8 * ((lane >> 3) & 1) + (lane & 7)) * 128;
    uint4* op = reinterpret_cast<uint4*>(P.out + (size_t)(128 * (2 * tp + (cs_ & 1)) + 32 * wq + 8 * wg + (lane >> 3)) * DM + 128 * (cs_ >> 1) + 64 * rank) + (lane & 7);
    float accK[32];
    uint32_t res[16];
    {
      mbar_wait(BAR(B_GF + 4), 0);
      mbar_wait(BAR(B_GF + 5), 0);
      const uint32_t a = sb + 9 * 16384 + wg * 8192 + ((lane & 7) + 8 * (lane >> 4)) * 128 + (((2 * wq + ((lane >> 3) & 1)) ^ (lane & 7)) << 4);
#pragma unroll
      for (int q = 0; q < 4; q++) ldsm4t(res + 4 * q, a + q * 2048);
    }
    uint64_t ta = udesc(dAa + 2 * 2048, P.hi_no), tb = udesc(dB + 2048, P.hi_sw);
    wg_wait<0>();
    reg_fence<64>(accB);
    if (lane == 0) mbar_arrive_cl(mapa(BAR(B_PFREE + wg), rank ^ 1));
    uint32_t snd[16];
#pragma unroll
    for (int e = 0; e < 16; e++) snd[e] = pack2(accB[32 + 2 * e], accB[32 + 2 * e + 1]);
    mbar_wait(BAR(B_PFREE + wg), 0);
#pragma unroll
    for (int q = 0; q < 4; q++) st_async4(rex + q * 2048, snd + 4 * q, rbar);
    mbar_wait(BAR(B_A16), 0);
    TL2(24);
    half_unit<4, true>(accK, ta, tb);
    mbar_wait(BAR(B_AF + 4), 0);
    half_unit<4, false>(accK, ta + 1024, tb + 512);
    ta = udesc(dAa + 3 * 2048, P.hi_no); tb = udesc(dB + 2048 + 1024, P.hi_sw);
    mbar_wait(BAR(B_AF + 5), 0);
    TL2(25);
    half_unit<8, false>(accK, ta, tb);
    SCHED_FENCE();
#pragma unroll
    for (int j = 0; j < 16; j++) { accB[2 * j] += blo(res[j]); accB[2 * j + 1] += bhi(res[j]); }
    reg_fence<32>(accB);
    ta = udesc(dAa + 5 * 2048, P.hi_no); tb = udesc(dB + 4 * 2048, P.hi_sw);
    const uint64_t tc = udesc(dAa + 5 * 2048 + 1024 - wg * 256, P.hi_no >> 1);
    mbar_wait(BAR(B_AF + 6), 0);
    TL2(26);
    {
      wg_fence();
#pragma unroll
      for (int ks = 0; ks < 4; ks++) wg_g2h(accK, ta + ks * 16, tb + ks * 128);
#pragma unroll
      for (int ks = 0; ks < 2; ks++) wg_g2h(accK, tc + ks * 16, tb + 512 + ks * 128);
      wg_commit();
      mbar_wait_cl(BAR(B_EXCH + wg), 0);
      TLW(1 + wg);
      uint4 v[4];
#pragma unroll
      for (int q = 0; q < 4; q++) v[q] = lds128(ex + q * 2048);
#pragma unroll
      for (int q = 0; q < 4; q++) {
        accB[8 * q] += blo(v[q].x); accB[8 * q + 1] += bhi(v[q].x); accB[8 * q + 2] += blo(v[q].y); accB[8 * q + 3] += bhi(v[q].y);
        accB[8 * q + 4] += blo(v[q].z); accB[8 * q + 5] += bhi(v[q].z); accB[8 * q + 6] += blo(v[q].w); accB[8 * q + 7] += bhi(v[q].w);
      }
      reg_fence<32>(accB);
    }
    wg_wait<0>();
    reg_fence<32>(accK);
    TLW(32 + wg);
#pragma unroll
    for (int q = 0; q < 4; q++)
      stsm4(rowa + (((2 * q + (lane >> 4)) ^ (lane & 7)) << 4), pack2(accB[8 * q] + accK[8 * q], accB[8 * q + 1] + accK[8 * q + 1]), pack2(accB[8 * q + 2] + accK[8 * q + 2], accB[8 * q + 3] + accK[8 * q + 3]),
            pack2(accB[8 * q + 4] + accK[8 * q + 4], accB[8 * q + 5] + accK[8 * q + 5]), pack2(accB[8 * q + 6] + accK[8 * q + 6], accB[8 * q + 7] + accK[8 * q + 7]));
    __syncwarp();
#pragma unroll
    for (int q = 0; q < 4; q++) {
      const int r = 4 * q + (lane >> 3);
      op[((q & 1) * 4 + (q >> 1) * 16) * (DM / 8)] = lds128(stg + r * 128 + (((lane & 7) ^ (r & 7)) << 4));
    }
    if (tid == 0) asm volatile("red.relaxed.gpu.global.add.u32 [%0], 1;" ::"l"(&P.cnt[C_DONE * CNT_STRIDE]) : "memory");
    TLW(34 + wg);
  } else {
    asm volatile("setmaxnreg.dec.sync.aligned.u32 56;");
    if (warp == 8 && elect_one()) {
#pragma unroll 1
      for (int j = 0; j < AHEAD; j++) LOAD_KV(j);
      mbar_expect(BAR(B_KFF), 8192);
      bulk_ld(sb + KRAW, P.ssmk + (size_t)(4 * mb) * S_LEN, 8192, BAR(B_KFF));
      TLONE(38);
    }
    __syncwarp();
    {
    FRESH_IDS();
    uint2 small;
    lds64(small.x, small.y, sb + SMALL + 32 + (lane >> 2) * 8);
    {
      trap_if(sb & 1023u);
      asm volatile("barrier.cluster.wait.aligned;" ::: "memory");
      const int wq = warp & 3, g = lane >> 2, t = lane & 3;
      const uint32_t lro = (tid & 127) * 16;
      const int G = 4 * rank + wq;
      const uint32_t rsb = mapa(sb, g >> 2);
      const uint32_t dU = rsb + UT + G * 256 + (g & 2) * 64 + (((g ^ G) & 1) << 6) + t * 16;
      const uint32_t w0 = prmt(small.x, small.x, 0x1010), w1 = prmt(small.x, small.x, 0x3232), w2 = prmt(small.y, small.y, 0x1010), w3 = prmt(small.y, small.y, 0x3232);
#pragma unroll 1
      for (int j = 0; j < 8; j++) {
        mbar_wait_aux(BAR(B_RAWF) + 8 * j, 0);
        uint32_t k0[4], k1[4], k2[4], k3[4], vv[4];
        const uint32_t ka = sb + RAWK + 128 + j * RAWK_BLK + lro;
        ldsm4t(k3, ka - 48); ldsm4t(k2, ka - 32); ldsm4t(k1, ka - 16); ldsm4t(k0, ka);
        ldsm4t(vv, sb + RAWV + j * 2048 + lro);
        if (wq == (j & 3) && elect_one()) {
          if (j + AHEAD < 8) LOAD_KV(j + AHEAD);
          if (j >= 4) LOAD_Q(j - 4);
          if (j == KFY_POS) {
            mbar_expect(BAR(B_KFF + 1), 8192);
            bulk_ld(sb + KRAW2, P.ssmk + (size_t)(4 * mb + 2) * S_LEN, 8192, BAR(B_KFF + 1));
          }
          if (j == RPK_LD) LOAD_RPK();
          if (j == QST_POS) {
            mbar_expect(BAR(B_QST), 16384);
            bulk_ld(sb + QST, P.qstat, 16384, BAR(B_QST));
          }
        }
#pragma unroll
        for (int i = 0; i < 4; i++) vv[i] = bmul2(bfma2(k0[i], w0, bfma2(k1[i], w1, bfma2(k2[i], w2, bmul2(k3[i], w3)))), vv[i]);
        st_async4(dU + j * 2048, vv, rsb + BARS + 8 * B_UF + 8 * (j >> 1));
      }
      TLW(36);
      const uint32_t dX = rsb + XT + G * 256 + (g & 2) * 64 + ((((g & 1) * 4 + t) ^ G) << 4);
      uint32_t x[8][4];
#pragma unroll
      for (int s = 0; s < 4; s++) {
        mbar_wait_aux(BAR(B_RAWQF + s), 0);
        TLW(28 + s);
        ldsm4t(x[2 * s], sb + RAWQ + s * 4096 + lro);
        ldsm4t(x[2 * s + 1], sb + RAWQ + s * 4096 + 2048 + lro);
        if (s > 0 && s < 3) {
          st_async4(dX + s * 4096 - 4096, x[2 * s - 2], rsb + BARS + 8 * B_XQF);
          st_async4(dX + s * 4096 - 2048, x[2 * s - 1], rsb + BARS + 8 * B_XQF);
        }
        if (s >= 2) {
          st_async4(dX + s * 4096, x[2 * s], rsb + BARS + 8 * B_XQF);
          st_async4(dX + s * 4096 + 2048, x[2 * s + 1], rsb + BARS + 8 * B_XQF);
        }
      }
      TLW(37);
      if (warp & 1) {
        mbar_wait_aux(BAR(B_KFF + 1), 0);
#pragma unroll
        for (int c = 0; c < 4; c++) {
          const int n = 32 * c + lane;
          filter_block(sb + KRAW2 + (warp & 2) * 2048 + n * 32, sb + KT + n * 128 + (((4 + (warp & 2)) ^ (lane & 7)) << 4));
        }
        fence_async_smem();
        __syncwarp();
        if (lane == 0) mbar_arrive(BAR(B_KT2));
      }
      __syncwarp();
      if (lane == 0) mbar_arrive(BAR(B_RAWDONE));
      TLW(52);
    }
    const unsigned ep = (done >> 7) + 1;
    FFN_ROLE();
    if (warp == 8) {
      if (elect_one()) {
        const CUtensorMap* tw = rank ? &P.tmWu : &P.tmWg;
        uint32_t slot = 0, par = 1;
#pragma unroll 1
        for (int u = 0; u < 18; u++) {
          const int c0 = 128 * (cs_ >> 1) + 64 * rank;
          if (u < 12) {
            if (u == 1) {
              mbar_wait_aux(BAR(B_PUB), 0);
              mbar_wait_aux(BAR(B_RPK), 0);
              asm volatile("cp.async.bulk.global.shared::cta.bulk_group [%0], [%1], 6144;\ncp.async.bulk.commit_group;" ::"l"(P.w3 + mb * 384), "r"(sb + RPK) : "memory");
            }
            if (u == 2) {
              asm volatile("cp.async.bulk.wait_group 0;" ::: "memory");
              mbar_arrive(BAR(B_SIG + 1));
              TLONE(59);
            }
            if (u == 1 || u == 2) mbar_wait_aux(BAR(B_RAWDONE - 1) + 8 * u, 0);
            if (u == 8) { mbar_wait_aux(BAR(B_H1), 0); fence_async(); }
            if (u == 4) l2_prefetch(P.wd + (size_t)mb * 5504, 11008);
            mbar_wait_aux(BAR(B_WE) + 8 * slot, par);
            const uint32_t fb = BAR(B_WF) + 8 * slot, dst = sb + WR + slot * 32768;
            const int q = u < 8 ? (u & 1) + ((u >> 1) & 2) : u - 8;
            mbar_expect(fb, u < 8 ? 32768 : 24576);
            if (u < 8) {
              const int col = 64 * (4 * (u & 2) + cs_);
              tma3d_mc(dst + rank * 8192, tw, fb, col, q, 0);
              tma3d_mc(dst + 16384 + rank * 8192, tw, fb, col, q, 64);
            } else {
              asm volatile("cp.async.bulk.shared::cluster.global.mbarrier::complete_tx::bytes.multicast::cluster [%0], [%1], %2, [%3], %4;" ::"r"(dst + rank * 12288),
                           "l"(P.w3 + (cs_ * 8 + 2 * q + rank) * 768), "r"(12288), "r"(fb), "h"((uint16_t)3) : "memory");
            }
            if (++slot == 3) { slot = 0; par ^= 1; }
            continue;
          }
          const int i = u - 12;
          if (i) mbar_wait_aux(BAR(B_UD) + 8 * ((G_AFTER >> (4 * i)) & 7), 0);
          const uint32_t fb = BAR(B_GF) + 8 * i, dst = sb + ((G_SLOTS >> (4 * i)) & 7) * 32768;
          mbar_expect(fb, 32768);
          if (i < 4) {
            const int k0 = 64 * (4 * i + rank);
            tma2d(dst, &P.tmWd, fb, c0, k0);
            tma2d(dst + 8192, &P.tmWd, fb, c0 ^ 64, k0);
            tma2d(dst + 16384, &P.tmWd, fb, c0, k0 + 128);
            tma2d(dst + 24576, &P.tmWd, fb, c0 ^ 64, k0 + 128);
          } else {
            tma2d(dst, &P.tmWd, fb, c0, 256 * i);
            tma2d(dst + 8192, &P.tmWd, fb, c0, 256 * i + 64);
            if (i == 4) {
              tma2d(dst + 16384, &P.tmWd, fb, c0, 256 * i + 128);
              tma2d(dst + 24576, &P.tmWd, fb, c0, 256 * i + 192);
            } else {
              const int s0 = 128 * (2 * tp + (cs_ & 1));
              tma3d(dst + 16384, &P.tmR, fb, s0, 0, c0 >> 2);
              tma3d(dst + 24576, &P.tmR, fb, s0 + 64, 0, c0 >> 2);
            }
          }
        }
      }
    } else if (warp == 9) {
      if (elect_one()) {
        const int s0 = 128 * (2 * tp + rank);
#pragma unroll 1
        for (int q = 0; q < 4; q++) {
          if (!(q & 1)) {
            mbar_wait_aux(BAR(B_RAWDONE) + 4 * q, 0);
            poll_cnt(&P.cnt[(C_H + (q >> 1)) * CNT_STRIDE], ep * 128);
            if (q) mbar_arrive(BAR(B_H1));
            fence_async();
          }
          const uint32_t fb = BAR(B_XF) + 8 * q, fb1 = q ? fb : BAR(B_X0B);
          mbar_expect(fb, q ? 32768 : 16384);
          if (!q) mbar_expect(fb1, 16384);
#pragma unroll
          for (int i = 0; i < 4; i++) tma2d(sb + XR + q * 32768 + (i & 1) * 16384 + (i >> 1) * 8192, &P.tmH, i < 2 ? fb : fb1, s0 + 64 * (i >> 1), 128 * q + 64 * (i & 1));
          TLONE(40 + q);
        }
        const int tile2 = 2 * tp + (cs_ & 1);
        const __nv_bfloat16* src = P.act + (size_t)tile2 * 22 * 8192;
#pragma unroll 1
        for (int i = 0; i < 7; i++) {
          if (!(i & 1) && i < 6) {
            mbar_wait_aux(BAR(B_SIG + 2) + 4 * i, 0);
            poll_cnt(&P.cnt[(C_A + tile2 * 3 + (i >> 1)) * CNT_STRIDE], ep * 8);
            fence_async();
            TLONE(48 + (i >> 1));
          }
          const uint32_t fb = BAR(B_AF) + 8 * i, dst = sb + ((A_SLOTS >> (4 * i)) & 7) * 32768;
          mbar_wait_aux(BAR(B_UD) + 8 * ((A_AFTER >> (4 * i)) & 7), 0);
          if (i == 4) {
            mbar_expect(BAR(B_A16), 16384);
            bulk_ld(dst, src + 16 * 8192, 16384, BAR(B_A16));
            mbar_expect(fb, 16384);
            bulk_ld(dst + 16384, src + 17 * 8192, 16384, fb);
            continue;
          }
          mbar_expect(fb, i < 6 ? 32768 : 24576);
          if (i < 4) {
            bulk_ld(dst, src + (4 * i + rank) * 8192, 16384, fb);
            bulk_ld(dst + 16384, src + (4 * i + 2 + rank) * 8192, 16384, fb);
          } else {
            bulk_ld(dst, src + (8 + 2 * i) * 8192, i < 6 ? 32768 : 24576, fb);
          }
        }
      }
    } else if (warp == 11) {
      uint32_t slot = 0, par = 0;
#pragma unroll 1
      for (int u = 0; u < 16; u++) {
        if (u == 6) mbar_wait_aux(BAR(B_CS), 0);
        if (u < 2) mbar_wait_aux(BAR(B_XF) + 8 * u, 0);
        if (u == 4 || u == 5) mbar_wait_aux(BAR(B_XF - 2) + 8 * u, 0);
        if (u < 12) mbar_wait_aux(BAR(B_WF) + 8 * slot, par);
        else { mbar_wait_aux(BAR(B_GF - 12) + 8 * u, 0); mbar_wait_aux(BAR(B_AF - 12) + 8 * u, 0); }
        nb_sync(NB_GATE, 288);
        if (++slot == 3) { slot = 0; par ^= 1; }
      }
    } else {
#pragma unroll 1
      for (int ev = 0; ev < 5; ev++) {
        if (ev == 2) {
#pragma unroll
          for (int i = 0; i < 4; i++) sts128(sb + CSM + i * 512 + lane * 16, 0, 0, 0, 0);
          __syncwarp();
          poll_cnt(&P.cnt[C_CS * CNT_STRIDE], ep * 4);
          const int col3 = 1024 + 8 * (cs_ < 7 ? 6 * cs_ : 40);
          uint32_t a[12];
#pragma unroll
          for (int i = 0; i < 12; i++) a[i] = __ldcg(P.colsum + (i & 3) * 704 + (i < 8 ? 256 * (i >> 2) + 32 * cs_ : col3 / 2) + lane);
#pragma unroll
          for (int i = 0; i < 12; i++) {
            const int r = 2 * (i >> 2) + (i & 1);
            const int cg = (i & 2) * (i < 8 ? 4 : 3) + (lane >> 2);
            if (i < 8 || (i & 2) || lane < 24) sts32(sb + CSM + (cg >> 3) * 1024 + r * 128 + (((cg & 7) ^ r) << 4) + (lane & 3) * 4, a[i]);
          }
          fence_async_smem();
          __syncwarp();
          if (lane == 0) mbar_arrive(BAR(B_CS));
          TLREC(58);
        }
        mbar_wait_aux(BAR(B_SIG) + 8 * ev, 0);
        if (lane == 0) red_release(&P.cnt[(ev < 2 ? C_H + ev : C_A + (2 * tp + rank) * 3 + ev - 2) * CNT_STRIDE]);
        __syncwarp();
        if (ev == 0 && lane < 2) mbar_arrive_cl(mapa(BAR(B_PUB), lane));
      }
    }
    }
  }
}

typedef CUresult (*EncFn)(CUtensorMap*, CUtensorMapDataType, cuuint32_t, void*, const cuuint64_t*, const cuuint64_t*, const cuuint32_t*,
                          const cuuint32_t*, CUtensorMapInterleave, CUtensorMapSwizzle, CUtensorMapL2promotion, CUtensorMapFloatOOBfill);

void enc(EncFn fn, CUtensorMap* tm, const void* ptr, int rank, const cuuint64_t* gd, const cuuint64_t* gs, const cuuint32_t* bd, bool sw) {
  cuuint32_t es[4] = {1, 1, 1, 1};
  fn(tm, CU_TENSOR_MAP_DATA_TYPE_BFLOAT16, rank, const_cast<void*>(ptr), gd, gs, bd, es, CU_TENSOR_MAP_INTERLEAVE_NONE,
     sw ? CU_TENSOR_MAP_SWIZZLE_128B : CU_TENSOR_MAP_SWIZZLE_NONE, CU_TENSOR_MAP_L2_PROMOTION_L2_128B, CU_TENSOR_MAP_FLOAT_OOB_FILL_NONE);
}

}

extern "C" void kernel_launch(void* const* d_in, const int* in_sizes, int n_in, void* d_out, int out_size) {
  (void)in_sizes; (void)n_in; (void)out_size;
  static EncFn fn = nullptr;
  static void *hT = nullptr, *act = nullptr, *qstat = nullptr, *cnt = nullptr, *colsum = nullptr, *hstat = nullptr, *w3 = nullptr;
  if (!fn) {
    void* f = nullptr;
    cudaDriverEntryPointQueryResult qr;
    cudaGetDriverEntryPoint("cuTensorMapEncodeTiled", &f, cudaEnableDefault, &qr);
    fn = (EncFn)f;
    cudaGetSymbolAddress(&hT, g_hT); cudaGetSymbolAddress(&act, g_act); cudaGetSymbolAddress(&qstat, g_qstat);
    cudaGetSymbolAddress(&cnt, g_cnt); cudaGetSymbolAddress(&colsum, g_colsum); cudaGetSymbolAddress(&hstat, g_hstat); cudaGetSymbolAddress(&w3, g_w3);
    cudaFuncSetAttribute(fused_kernel, cudaFuncAttributeMaxDynamicSharedMemorySize, SMEM_TOTAL);
  }
  Params P;
  P.q = (const __nv_bfloat16*)d_in[0];
  P.hT = (__nv_bfloat16*)hT; P.act = (__nv_bfloat16*)act; P.qstat = (uint4*)qstat; P.cnt = (unsigned*)cnt; P.colsum = (unsigned*)colsum; P.hstat = (uint4*)hstat; P.w3 = (uint4*)w3;
  P.shiftk = (const __nv_bfloat16*)d_in[3]; P.ssmk = (const __nv_bfloat16*)d_in[4]; P.ssmD = (const __nv_bfloat16*)d_in[5];
  P.wd = (const __nv_bfloat16*)d_in[9];
  P.zero = 0; P.hi_sw = 0x40000040u; P.hi_no = 0x40u; P.hi_w3 = 0x20u;
  P.out = (__nv_bfloat16*)d_out;
  {
    cuuint64_t gd[2] = {DM, S_LEN}, gs[1] = {DM * 2};
    cuuint32_t bk[2] = {8, 136}, bv[2] = {8, 128};
    enc(fn, &P.tmK, d_in[1], 2, gd, gs, bk, false);
    enc(fn, &P.tmV, d_in[2], 2, gd, gs, bv, false);
    enc(fn, &P.tmQ, P.q, 2, gd, gs, bv, false);
  }
  {
    cuuint64_t gd[3] = {FF, 4, 128}, gs[2] = {FF * 2, FF * 8};
    cuuint32_t bd[3] = {64, 1, 64};
    enc(fn, &P.tmWg, d_in[7], 3, gd, gs, bd, true);
    enc(fn, &P.tmWu, d_in[8], 3, gd, gs, bd, true);
  }
  {
    cuuint64_t gd[4] = {8, 128, FF / 8, 4}, gs[3] = {FF * 8, 16, FF * 2};
    cuuint32_t bd[4] = {8, 32, 6, 1};
    enc(fn, &P.tmG3, d_in[7], 4, gd, gs, bd, false);
    enc(fn, &P.tmU3, d_in[8], 4, gd, gs, bd, false);
  }
  {
    cuuint64_t gd[2] = {DM, FF}, gs[1] = {DM * 2};
    cuuint32_t bd[2] = {64, 64};
    enc(fn, &P.tmWd, P.wd, 2, gd, gs, bd, true);
  }
  {
    cuuint64_t gd[2] = {S_LEN, DM}, gs[1] = {S_LEN * 2};
    cuuint32_t bd[2] = {64, 64};
    enc(fn, &P.tmH, hT, 2, gd, gs, bd, true);
  }
  {
    cuuint64_t gd[3] = {S_LEN, 4, 128}, gs[2] = {128 * S_LEN * 2, S_LEN * 2};
    cuuint32_t bd[3] = {64, 4, 16};
    enc(fn, &P.tmR, hT, 3, gd, gs, bd, true);
  }
  fused_kernel<<<NHELP + NMAIN, 384, SMEM_TOTAL, cudaStreamPerThread>>>(P);
}
```
